```python
import torch

def _softmax(x, axis=-1):
    return torch.softmax(x, dim=axis)
def _gelu(x):
    return torch.nn.functional.gelu(x, approximate="tanh")
def _silu(x):
    return torch.nn.functional.silu(x)
def _sigmoid(x):
    return torch.sigmoid(x)
def _layernorm(x, axis=-1, eps=1e-5):
    m = x.mean(dim=axis, keepdim=True)
    v = x.var(dim=axis, keepdim=True, unbiased=False)
    return (x - m) / torch.sqrt(v + eps)
def _scatter_add(tgt, idx, src, axis=0):
    return tgt.clone().index_add_(axis, idx, src)
def _segment_sum(src, seg, n):
    out = torch.zeros((n,) + src.shape[1:], dtype=src.dtype)
    return out.index_add_(0, seg, src)
def _pad(x, pw):
    flat = tuple(v for pair in reversed(pw) for v in pair)
    return torch.nn.functional.pad(x, flat)

kernel_name = 'parallel_sum__sliding_block_cached__dense_activation_mish__decode'

def setup_inputs():

    _w = (lambda a: (lambda t: t.to(torch.bfloat16) if t.is_floating_point() else t)(torch.as_tensor(a)))
    def _A_setup():
        B, Sq, D = 2, 1, 512
        Hq, Hkv, Sk, Dh = 32, 8, 8192, 128
        assert Hq % Hkv == 0, (Hq, Hkv)
        return {
            "x": _w((lambda *s: torch.randn(*s, dtype=torch.bfloat16) * 0.05)(B, Sq, D)),
            "k_cache": _w((lambda *s: torch.randn(*s, dtype=torch.bfloat16) * 1.6)(B, Hkv, Sk, Dh)),
            "v_cache": _w((lambda *s: torch.randn(*s, dtype=torch.bfloat16) * 0.4)(B, Hkv, Sk, Dh)),
            "wq": _w((lambda *s: torch.randn(*s, dtype=torch.bfloat16) * 1.6)(D, Hq * Dh) * (D ** -0.5)),
            "wo": _w((lambda *s: torch.randn(*s, dtype=torch.bfloat16) * 0.4)(Hq * Dh, D) * ((Hq * Dh) ** -0.5)),
        }
    _A_in = _A_setup()

    def _B_setup():
        B, S, D, F = 2, 1, 512, 1792
        return {
            "x": _w((lambda *s: torch.randn(*s, dtype=torch.bfloat16) * 0.05)(B, S, D)),
            "w1": _w((lambda *s: torch.randn(*s, dtype=torch.bfloat16) * 0.8)(D, F) * (D ** -0.5)),
            "b1": _w((lambda *s: torch.randn(*s, dtype=torch.bfloat16) * 0.2)(F)),
            "w2": _w((lambda *s: torch.randn(*s, dtype=torch.bfloat16) * 0.1)(F, D) * (F ** -0.5)),
        }
    _B_in = _B_setup()

    return {
        "A_x": _A_in["x"],
        "A_k_cache": _A_in["k_cache"],
        "A_v_cache": _A_in["v_cache"],
        "A_wq": _A_in["wq"],
        "A_wo": _A_in["wo"],
        "B_x": _B_in["x"],
        "B_w1": _B_in["w1"],
        "B_b1": _B_in["b1"],
        "B_w2": _B_in["w2"],
    }

def reference(A_x, A_k_cache, A_v_cache, A_wq, A_wo, B_x, B_w1, B_b1, B_w2):
    def _A_ref(x, k_cache, v_cache, wq, wo):
        B, Sq, D = x.shape
        Hq, Dh = 32, 128
        Hkv, Sk = k_cache.shape[1], k_cache.shape[2]
        W = min(4096, max(256, Sk // 4))
        rep = Hq // Hkv
        q = (lambda x, *d: x.permute(*d))((x @ wq).reshape(B, Sq, Hq, Dh), 0, 2, 1, 3)
        k = (lambda x, n, axis: torch.repeat_interleave(x, n, dim=axis))(k_cache[:, :, Sk - W:, :], rep, axis=1)
        v = (lambda x, n, axis: torch.repeat_interleave(x, n, dim=axis))(v_cache[:, :, Sk - W:, :], rep, axis=1)
        scores = torch.einsum("bhqd,bhkd->bhqk", q, k) * (Dh ** -0.5)
        p = _softmax(scores, axis=-1)
        o = torch.einsum("bhqk,bhkd->bhqd", p, v)
        return (lambda x, *d: x.permute(*d))(o, 0, 2, 1, 3).reshape(B, Sq, Hq * Dh) @ wo

    def _B_ref(x, w1, b1, w2):
        h = torch.einsum("bsd,df->bsf", x, w1) + b1
        sp = torch.log1p(torch.exp(-torch.abs(h))) + torch.where(h > 0, h, torch.zeros_like(h))
        act = h * torch.tanh(sp)
        return torch.einsum("bsf,fd->bsd", act, w2)

    x = A_x
    xn = _layernorm(x, axis=-1)
    return x + _A_ref(xn, A_k_cache, A_v_cache, A_wq, A_wo) + _B_ref(xn, B_w1, B_b1, B_w2)
```

```cpp
#include <cuda_runtime.h>
#include <cuda_bf16.h>
#include <cuda.h>
#include <stdint.h>

namespace {

constexpr int D_MODEL = 512;
constexpr int SK = 8192;
constexpr int WIN = 2048;
constexpr int WIN0 = SK - WIN;
constexpr int FF = 1792;

constexpr int NCTA = 128;
constexpr int NCW = 16;
constexpr int NTHREADS = (NCW + 1) * 32;

constexpr int SM_WQ = 0;
constexpr int SM_K = SM_WQ + 32768;
constexpr int SM_V = SM_K + 65536;
constexpr int SM_W1 = SM_V + 65536;
constexpr int SM_WO = SM_W1 + 16384;
constexpr int SM_W2 = SM_WO + 32768;
constexpr int SM_BAR = SM_W2 + 14336;
constexpr int SM_Q = SM_BAR + 256;
constexpr int SM_STAT = SM_Q + 1024;
constexpr int SM_EPOCH = SM_STAT + 512;
constexpr int SM_TOTAL = SM_EPOCH + 16;

constexpr int CH_WQ = 0, CH_K = 4, CH_V = 12, CH_W1 = 20, CH_WO = 22, CH_W2 = 26, NCHUNK = 28;
constexpr int WINDOW = 8;

constexpr unsigned SPIN_LIMIT = 1u << 22;

struct Scratch {
    unsigned epoch;
    unsigned pad[31];
    unsigned long long qx[2 * 32 * 64];
    unsigned long long sx[16 * 128 * 32];
    unsigned long long ox[2 * 256 * 8];
    unsigned long long ax[2 * 112 * 8];
    unsigned long long px[16 * 8 * 64];
};

__device__ Scratch g_scratch;

struct Params {
    CUtensorMap wq, k, v, w1, wo, w2;
    const __nv_bfloat16* x;
    const __nv_bfloat16* b1;
    __nv_bfloat16* out;
    Scratch* sc;
};

__device__ __forceinline__ uint32_t smem_u32(const void* p) { return (uint32_t)__cvta_generic_to_shared(p); }
__device__ __forceinline__ void mbar_init(uint32_t bar, uint32_t cnt) {
    asm volatile("mbarrier.init.shared::cta.b64 [%0], %1;" ::"r"(bar), "r"(cnt) : "memory");
}
__device__ __forceinline__ void mbar_expect_tx(uint32_t bar, uint32_t bytes) {
    asm volatile("mbarrier.arrive.expect_tx.shared::cta.b64 _, [%0], %1;" ::"r"(bar), "r"(bytes) : "memory");
}
__device__ __forceinline__ void mbar_wait(uint32_t bar) {
    unsigned n = 0;
    uint32_t ok;
    do {
        asm volatile("{\n.reg .pred p;\nmbarrier.try_wait.parity.shared::cta.b64 p, [%1], 0;\nselp.u32 %0, 1, 0, p;\n}"
                     : "=r"(ok) : "r"(bar) : "memory");
    } while (!ok && ++n < SPIN_LIMIT);
}
__device__ __forceinline__ void tma2d(uint32_t dst, const CUtensorMap* tm, int c0, int c1, uint32_t bar) {
    asm volatile("cp.async.bulk.tensor.2d.shared::cluster.global.mbarrier::complete_tx::bytes [%0], [%1, {%3, %4}], [%2];"
                 ::"r"(dst), "l"((uint64_t)tm), "r"(bar), "r"(c0), "r"(c1) : "memory");
}
__device__ __forceinline__ void bar_sync(int id, int n) { asm volatile("bar.sync %0, %1;" ::"r"(id), "r"(n) : "memory"); }
__device__ __forceinline__ void bar_arrive(int id, int n) { asm volatile("bar.arrive %0, %1;" ::"r"(id), "r"(n) : "memory"); }

__device__ __forceinline__ void ldsm4(uint32_t (&r)[4], uint32_t addr) {
    asm volatile("ldmatrix.sync.aligned.m8n8.x4.shared.b16 {%0,%1,%2,%3}, [%4];"
                 : "=r"(r[0]), "=r"(r[1]), "=r"(r[2]), "=r"(r[3]) : "r"(addr) : "memory");
}
__device__ __forceinline__ void ldsm4t(uint32_t (&r)[4], uint32_t addr) {
    asm volatile("ldmatrix.sync.aligned.m8n8.x4.trans.shared.b16 {%0,%1,%2,%3}, [%4];"
                 : "=r"(r[0]), "=r"(r[1]), "=r"(r[2]), "=r"(r[3]) : "r"(addr) : "memory");
}
__device__ __forceinline__ void mma16816(float (&c)[4], uint32_t a0, uint32_t a1, uint32_t a2, uint32_t a3, uint32_t b0, uint32_t b1) {
    asm volatile("mma.sync.aligned.m16n8k16.row.col.f32.bf16.bf16.f32 {%0,%1,%2,%3}, {%4,%5,%6,%7}, {%8,%9}, {%0,%1,%2,%3};"
                 : "+f"(c[0]), "+f"(c[1]), "+f"(c[2]), "+f"(c[3])
                 : "r"(a0), "r"(a1), "r"(a2), "r"(a3), "r"(b0), "r"(b1));
}
__device__ __forceinline__ void st_ll1(unsigned long long* p, uint32_t d, uint32_t tag) {
    unsigned long long w = ((unsigned long long)tag << 32) | d;
    asm volatile("st.relaxed.gpu.global.b64 [%0], %1;" ::"l"(p), "l"(w) : "memory");
}
__device__ __forceinline__ void st_ll2(unsigned long long* p, uint32_t d0, uint32_t d1, uint32_t tag) {
    unsigned long long w0 = ((unsigned long long)tag << 32) | d0, w1 = ((unsigned long long)tag << 32) | d1;
    asm volatile("st.relaxed.gpu.global.v2.b64 [%0], {%1, %2};" ::"l"(p), "l"(w0), "l"(w1) : "memory");
}
__device__ __forceinline__ void ld_ll2(const unsigned long long* p, unsigned long long& w0, unsigned long long& w1) {
    asm volatile("ld.relaxed.gpu.global.v2.b64 {%0, %1}, [%2];" : "=l"(w0), "=l"(w1) : "l"(p) : "memory");
}
__device__ __forceinline__ float bf16r(float x) { return __bfloat162float(__float2bfloat16_rn(x)); }
__device__ __forceinline__ uint32_t pack_bf16(float lo, float hi) {
    __nv_bfloat162 v = __floats2bfloat162_rn(lo, hi);
    return *reinterpret_cast<uint32_t*>(&v);
}
__device__ __forceinline__ float bf_lo(uint32_t u) { return __uint_as_float(u << 16); }
__device__ __forceinline__ float bf_hi(uint32_t u) { return __uint_as_float(u & 0xffff0000u); }
__device__ __forceinline__ float2 lds_f2(uint32_t a) {
    float2 v;
    asm volatile("ld.shared.v2.f32 {%0, %1}, [%2];" : "=f"(v.x), "=f"(v.y) : "r"(a) : "memory");
    return v;
}
__device__ __forceinline__ void sts_f1(uint32_t a, float v) { asm volatile("st.shared.f32 [%0], %1;" ::"r"(a), "f"(v) : "memory"); }
__device__ __forceinline__ void sts_u1(uint32_t a, uint32_t v) { asm volatile("st.shared.u32 [%0], %1;" ::"r"(a), "r"(v) : "memory"); }
__device__ __forceinline__ void sts_f2(uint32_t a, float x, float y) {
    asm volatile("st.shared.v2.f32 [%0], {%1, %2};" ::"r"(a), "f"(x), "f"(y) : "memory");
}

#define TS(i) do { } while (0)

__global__ void __launch_bounds__(NTHREADS, 1) fused_decode_kernel(const __grid_constant__ Params p) {
    extern __shared__ __align__(1024) uint8_t smem[];
    const uint32_t sb = smem_u32(smem);
    const int c = blockIdx.x;
    const int warp = threadIdx.x >> 5, lane = threadIdx.x & 31;
    const int bh = c >> 3, j = c & 7;
    const int r = c >> 4, g16 = c & 15;

    if (warp == NCW) {
        if (lane < NCHUNK) mbar_init(sb + SM_BAR + lane * 8, 1);
        asm volatile("fence.proxy.async.shared::cta;" ::: "memory");
        __syncwarp();
        bar_arrive(1, NTHREADS);
        if (lane == 0) {
            const int krow = bh * SK + WIN0;
#pragma unroll
            for (int i = 0; i < NCHUNK; i++) {
                const uint32_t bar = sb + SM_BAR + i * 8;
                if (i >= WINDOW) mbar_wait(bar - WINDOW * 8);
                if (i < CH_K) {
                    mbar_expect_tx(bar, 8192);
                    tma2d(sb + SM_WQ + i * 8192, &p.wq, 32 * c, 128 * i, bar);
                } else if (i < CH_V) {
                    const int q = i - CH_K;
                    mbar_expect_tx(bar, 8192);
                    tma2d(sb + SM_K + q * 8192, &p.k, 0, krow + j * 256 + q * 32, bar);
                    tma2d(sb + SM_K + q * 8192 + 4096, &p.k, 64, krow + j * 256 + q * 32, bar);
                } else if (i < CH_W1) {
                    const int q = i - CH_V;
                    mbar_expect_tx(bar, 8192);
                    tma2d(sb + SM_V + q * 8192, &p.v, 16 * j, krow + q * 256, bar);
                } else if (i < CH_WO) {
                    const int q = i - CH_W1;
                    if (c < 112) {
                        mbar_expect_tx(bar, 8192);
                        tma2d(sb + SM_W1 + q * 8192, &p.w1, 16 * c, 256 * q, bar);
                    } else {
                        mbar_expect_tx(bar, 0);
                    }
                } else if (i < CH_W2) {
                    const int q = i - CH_WO;
                    mbar_expect_tx(bar, 8192);
                    tma2d(sb + SM_WO + q * 8192, &p.wo, 32 * g16, 512 * r + 128 * q, bar);
                } else {
                    const int q = i - CH_W2;
                    mbar_expect_tx(bar, 7168);
                    tma2d(sb + SM_W2 + q * 7168, &p.w2, 32 * g16, 224 * r + 112 * q, bar);
                }
                TS(i);
            }
        }
        return;
    }

    const int u = warp;
    const int fg = lane >> 2, ft = lane & 3;
    Scratch* const sc = p.sc;

    uint32_t xb[4] = {0u, 0u, 0u, 0u};
    uint32_t xres = 0;
    uint32_t b1pair = 0;
    {
        const uint4* x4 = reinterpret_cast<const uint4*>(p.x);
        uint4 v0 = __ldg(x4 + lane * 2), v1 = __ldg(x4 + lane * 2 + 1);
        uint4 w0 = __ldg(x4 + 64 + lane * 2), w1 = __ldg(x4 + 64 + lane * 2 + 1);
        const uint32_t* x1 = reinterpret_cast<const uint32_t*>(p.x);
        uint32_t xr[4] = {0u, 0u, 0u, 0u};
        if (fg < 2) {
#pragma unroll
            for (int i = 0; i < 4; i++) xr[i] = __ldg(x1 + fg * 256 + u * 16 + i * 4 + ft);
        }
        if (u == 0) {
            xres = __ldg(x1 + (lane >> 4) * 256 + g16 * 16 + (lane & 15));
            if (lane == 0) sts_u1(sb + SM_EPOCH, *reinterpret_cast<volatile unsigned*>(&sc->epoch) + 1u);
        }
        if (u == 1 && c < 112) b1pair = __ldg(reinterpret_cast<const uint32_t*>(p.b1) + c * 8 + (lane & 7));
        const uint32_t a[8] = {v0.x, v0.y, v0.z, v0.w, v1.x, v1.y, v1.z, v1.w};
        const uint32_t b[8] = {w0.x, w0.y, w0.z, w0.w, w1.x, w1.y, w1.z, w1.w};
        float s0 = 0.f, s1 = 0.f;
#pragma unroll
        for (int i = 0; i < 8; i++) { s0 += bf_lo(a[i]) + bf_hi(a[i]); s1 += bf_lo(b[i]) + bf_hi(b[i]); }
#pragma unroll
        for (int o = 16; o > 0; o >>= 1) { s0 += __shfl_xor_sync(~0u, s0, o); s1 += __shfl_xor_sync(~0u, s1, o); }
        const float m0 = s0 * (1.f / D_MODEL), m1 = s1 * (1.f / D_MODEL);
        float q0 = 0.f, q1 = 0.f;
#pragma unroll
        for (int i = 0; i < 8; i++) {
            float d;
            d = bf_lo(a[i]) - m0; q0 += d * d; d = bf_hi(a[i]) - m0; q0 += d * d;
            d = bf_lo(b[i]) - m1; q1 += d * d; d = bf_hi(b[i]) - m1; q1 += d * d;
        }
#pragma unroll
        for (int o = 16; o > 0; o >>= 1) { q0 += __shfl_xor_sync(~0u, q0, o); q1 += __shfl_xor_sync(~0u, q1, o); }
        const float mean = bf16r(fg == 0 ? m0 : m1);
        const float var = bf16r((fg == 0 ? q0 : q1) * (1.f / D_MODEL));
        const float den = bf16r(sqrtf(bf16r(var + 1e-5f)));
        if (fg < 2) {
#pragma unroll
            for (int i = 0; i < 4; i++)
                xb[i] = pack_bf16(bf16r(bf_lo(xr[i]) - mean) / den, bf16r(bf_hi(xr[i]) - mean) / den);
        }
    }
    TS(0);

    const int lrow = (lane & 7) + ((lane >> 4) << 3);
    const int lchk = (lane >> 3) & 1;

    bar_sync(1, NTHREADS);
    const uint32_t tag = *reinterpret_cast<volatile uint32_t*>(smem + SM_EPOCH);
    {
        mbar_wait(sb + SM_BAR + (CH_WQ + (u >> 2)) * 8);
        TS(1);
        float acc[2][4] = {};
#pragma unroll
        for (int ks = 0; ks < 2; ks++) {
            const int row = u * 32 + ks * 16 + lrow;
#pragma unroll
            for (int mt = 0; mt < 2; mt++) {
                uint32_t a[4];
                ldsm4t(a, sb + SM_WQ + row * 64 + (((mt * 2 + lchk) ^ ((row >> 1) & 3)) << 4));
                mma16816(acc[mt], a[0], a[1], a[2], a[3], xb[ks * 2], xb[ks * 2 + 1]);
            }
        }
        __syncwarp();
        if (ft == 0) {
            const uint32_t rb = sb + SM_WQ + u * 2048;
#pragma unroll
            for (int mt = 0; mt < 2; mt++) {
                sts_f1(rb + (mt * 16 + fg) * 4, acc[mt][0]);
                sts_f1(rb + 128 + (mt * 16 + fg) * 4, acc[mt][1]);
                sts_f1(rb + (mt * 16 + fg + 8) * 4, acc[mt][2]);
                sts_f1(rb + 128 + (mt * 16 + fg + 8) * 4, acc[mt][3]);
            }
        }
    }
    bar_sync(2, NCW * 32);
    if (u == 0) {
        float2 s = make_float2(0.f, 0.f);
#pragma unroll
        for (int w = 0; w < NCW; w++) {
            float2 v = lds_f2(sb + SM_WQ + w * 2048 + lane * 8);
            s.x += v.x; s.y += v.y;
        }
        st_ll1(&sc->qx[((lane >> 4) * 32 + (c >> 2)) * 64 + (c & 3) * 16 + (lane & 15)], pack_bf16(s.x, s.y), tag);
        TS(2);
    } else if (u >= 4 && u < 8) {
        const int i = (u - 4) * 32 + lane;
        const unsigned long long* src = &sc->qx[((bh >> 3) * 32 + (bh & 7) * 4) * 64 + 2 * i];
        unsigned long long w0, w1;
        unsigned n = 0;
        do { ld_ll2(src, w0, w1); } while (((uint32_t)(w0 >> 32) != tag || (uint32_t)(w1 >> 32) != tag) && ++n < SPIN_LIMIT);
        const int head = i >> 5, pair = (2 * i) & 63;
        const int slot = pair >> 2, t = pair & 3;
        sts_u1(sb + SM_Q + ((head * 4 + t) * 16 + slot) * 4, (uint32_t)w0);
        sts_u1(sb + SM_Q + ((head * 4 + t + 1) * 16 + slot) * 4, (uint32_t)w1);
        TS(2);
    }
    bar_sync(2, NCW * 32);
    TS(3);

    {
        uint32_t qa[16];
        if (fg < 4) {
#pragma unroll
            for (int i = 0; i < 4; i++)
                asm volatile("ld.shared.v4.u32 {%0,%1,%2,%3}, [%4];"
                             : "=r"(qa[4 * i]), "=r"(qa[4 * i + 1]), "=r"(qa[4 * i + 2]), "=r"(qa[4 * i + 3])
                             : "r"(sb + SM_Q + (fg * 4 + ft) * 64 + i * 16) : "memory");
        } else {
#pragma unroll
            for (int i = 0; i < 16; i++) qa[i] = 0u;
        }
        mbar_wait(sb + SM_BAR + (CH_K + (u >> 1)) * 8);
        TS(4);
        float acc[2][4] = {};
        const uint32_t kb = sb + SM_K + (u >> 1) * 8192;
#pragma unroll
        for (int nt = 0; nt < 2; nt++) {
            const int row = (u & 1) * 16 + nt * 8 + (lane & 7);
#pragma unroll
            for (int q = 0; q < 4; q++) {
                const int chunk = q * 4 + (lane >> 3);
                uint32_t b[4];
                ldsm4(b, kb + (chunk >> 3) * 4096 + row * 128 + (((chunk & 7) ^ (row & 7)) << 4));
                mma16816(acc[nt], qa[4 * q], 0u, qa[4 * q + 1], 0u, b[0], b[1]);
                mma16816(acc[nt], qa[4 * q + 2], 0u, qa[4 * q + 3], 0u, b[2], b[3]);
            }
        }
        if (lane < 16) {
            const float scale = 0.08838834764831845f;
            const uint32_t d0 = pack_bf16(bf16r(acc[0][0]) * scale, bf16r(acc[0][1]) * scale);
            const uint32_t d1 = pack_bf16(bf16r(acc[1][0]) * scale, bf16r(acc[1][1]) * scale);
            st_ll2(&sc->sx[((bh * 128 + j * 16 + u) * 16 + lane) * 2], d0, d1, tag);
        }
        TS(5);
    }

    uint32_t pb[4][2];
    {
        unsigned long long w[4][2];
        const unsigned long long* src = &sc->sx[((bh * 128 + u * 8) * 16 + lane) * 2];
        unsigned n = 0;
        bool ok;
        do {
            ok = true;
#pragma unroll
            for (int i = 0; i < 4; i++) ld_ll2(src + i * 64, w[i][0], w[i][1]);
#pragma unroll
            for (int i = 0; i < 4; i++) ok = ok && (uint32_t)(w[i][0] >> 32) == tag && (uint32_t)(w[i][1] >> 32) == tag;
        } while (!ok && ++n < SPIN_LIMIT);
        __syncwarp();
        TS(6);
        float s[16];
#pragma unroll
        for (int i = 0; i < 4; i++) {
            s[4 * i] = bf_lo((uint32_t)w[i][0]); s[4 * i + 1] = bf_hi((uint32_t)w[i][0]);
            s[4 * i + 2] = bf_lo((uint32_t)w[i][1]); s[4 * i + 3] = bf_hi((uint32_t)w[i][1]);
        }
        float m = s[0];
#pragma unroll
        for (int i = 1; i < 16; i++) m = fmaxf(m, s[i]);
        m = fmaxf(m, __shfl_xor_sync(~0u, m, 1));
        m = fmaxf(m, __shfl_xor_sync(~0u, m, 2));
        m = fmaxf(m, __shfl_xor_sync(~0u, m, 16));
        const float LOG2E = 1.4426950408889634f;
        float l = 0.f;
#pragma unroll
        for (int i = 0; i < 16; i++) { s[i] = exp2f((s[i] - m) * LOG2E); l += s[i]; }
        l += __shfl_xor_sync(~0u, l, 1);
        l += __shfl_xor_sync(~0u, l, 2);
        l += __shfl_xor_sync(~0u, l, 16);
        const int head = fg & 3;
        if (lane < 16 && ft == 0) sts_f2(sb + SM_STAT + (u * 4 + head) * 8, m, l);
        bar_sync(2, NCW * 32);
        float2 st[NCW];
#pragma unroll
        for (int w2 = 0; w2 < NCW; w2++) st[w2] = lds_f2(sb + SM_STAT + (w2 * 4 + head) * 8);
        float gm = st[0].x;
#pragma unroll
        for (int w2 = 1; w2 < NCW; w2++) gm = fmaxf(gm, st[w2].x);
        float gl = 0.f;
#pragma unroll
        for (int w2 = 0; w2 < NCW; w2++) gl += st[w2].y * exp2f((st[w2].x - gm) * LOG2E);
        const float f = exp2f((m - gm) * LOG2E) / gl;
#pragma unroll
        for (int i = 0; i < 4; i++) {
            pb[i][0] = pack_bf16(s[4 * i] * f, s[4 * i + 1] * f);
            pb[i][1] = pack_bf16(s[4 * i + 2] * f, s[4 * i + 3] * f);
        }
        TS(7);
    }

    {
        mbar_wait(sb + SM_BAR + (CH_V + (u >> 1)) * 8);
        TS(8);
        float accE[4] = {}, accO[4] = {};
#pragma unroll
        for (int i = 0; i < 4; i++) {
            uint32_t a[4], a2[4];
            const int row = u * 128 + i * 32 + lrow;
            const uint32_t addr = sb + SM_V + row * 32 + ((lchk ^ ((row >> 2) & 1)) << 4);
            ldsm4t(a, addr);
            ldsm4t(a2, addr + 512);
            mma16816(accE, a[0], a[1], a[2], a[3], pb[i][0], pb[i][1]);
            mma16816(accO, a2[0], a2[1], a2[2], a2[3], pb[i][0], pb[i][1]);
        }
#pragma unroll
        for (int i = 0; i < 4; i++) accE[i] += __shfl_xor_sync(~0u, accO[i], 2);
        __syncwarp();
        if (ft < 2) {
            const uint32_t rb = sb + SM_V + u * 4096;
            sts_f1(rb + ((2 * ft) * 16 + fg) * 4, accE[0]);
            sts_f1(rb + ((2 * ft + 1) * 16 + fg) * 4, accE[1]);
            sts_f1(rb + ((2 * ft) * 16 + fg + 8) * 4, accE[2]);
            sts_f1(rb + ((2 * ft + 1) * 16 + fg + 8) * 4, accE[3]);
        }
        bar_sync(2, NCW * 32);
        if (u == 0) {
            float2 s = make_float2(0.f, 0.f);
#pragma unroll
            for (int w = 0; w < NCW; w++) {
                float2 v = lds_f2(sb + SM_V + w * 4096 + lane * 8);
                s.x += v.x; s.y += v.y;
            }
            const int head = (bh & 7) * 4 + (lane >> 3), dp = lane & 7;
            st_ll1(&sc->ox[(((bh >> 3) * 256 + head * 8 + j) * 4 + (dp & 3)) * 2 + (dp >> 2)], pack_bf16(s.x, s.y), tag);
            TS(9);
        }
    }

    if (c < 112) {
        mbar_wait(sb + SM_BAR + (CH_W1 + (u >> 3)) * 8);
        TS(10);
        float acc[4] = {};
#pragma unroll
        for (int ks = 0; ks < 2; ks++) {
            const int row = u * 32 + ks * 16 + lrow;
            uint32_t a[4];
            ldsm4t(a, sb + SM_W1 + row * 32 + ((lchk ^ ((row >> 2) & 1)) << 4));
            mma16816(acc, a[0], a[1], a[2], a[3], xb[ks * 2], xb[ks * 2 + 1]);
        }
        __syncwarp();
        if (ft == 0) {
            const uint32_t rb = sb + SM_W1 + u * 1024;
            sts_f1(rb + fg * 4, acc[0]);
            sts_f1(rb + 64 + fg * 4, acc[1]);
            sts_f1(rb + (fg + 8) * 4, acc[2]);
            sts_f1(rb + 64 + (fg + 8) * 4, acc[3]);
        }
        bar_sync(2, NCW * 32);
        if (u == 1 && lane < 16) {
            float2 s = make_float2(0.f, 0.f);
#pragma unroll
            for (int w = 0; w < NCW; w++) {
                float2 v = lds_f2(sb + SM_W1 + w * 1024 + lane * 8);
                s.x += v.x; s.y += v.y;
            }
            float h[2] = {bf16r(bf16r(s.x) + bf_lo(b1pair)), bf16r(bf16r(s.y) + bf_hi(b1pair))};
            float a[2];
#pragma unroll
            for (int i = 0; i < 2; i++) {
                const float e = bf16r(__expf(-fabsf(h[i])));
                const float sp = bf16r(bf16r(log1pf(e)) + fmaxf(h[i], 0.f));
                a[i] = h[i] * bf16r(tanhf(sp));
            }
            const int dp = lane & 7;
            st_ll1(&sc->ax[(((lane >> 3) * 112 + c) * 4 + (dp & 3)) * 2 + (dp >> 2)], pack_bf16(a[0], a[1]), tag);
            TS(11);
        }
    }

    {
        unsigned long long w[3][2] = {};
        if (lane < 8) {
            const unsigned long long* so = &sc->ox[((fg * 256 + r * 32 + u * 2) * 4 + ft) * 2];
            const unsigned long long* sa = &sc->ax[((fg * 112 + r * 14 + (u < 14 ? u : 0)) * 4 + ft) * 2];
            unsigned n = 0;
            bool ok;
            do {
                ld_ll2(so, w[0][0], w[0][1]);
                ld_ll2(so + 8, w[1][0], w[1][1]);
                ld_ll2(sa, w[2][0], w[2][1]);
                ok = true;
#pragma unroll
                for (int i = 0; i < 3; i++) ok = ok && (uint32_t)(w[i][0] >> 32) == tag && (uint32_t)(w[i][1] >> 32) == tag;
            } while (!ok && ++n < SPIN_LIMIT);
        }
        __syncwarp();
        TS(12);
        float acc[2][4] = {};
        mbar_wait(sb + SM_BAR + (CH_WO + (u >> 2)) * 8);
        TS(13);
#pragma unroll
        for (int ks = 0; ks < 2; ks++) {
            const int row = u * 32 + ks * 16 + lrow;
#pragma unroll
            for (int mt = 0; mt < 2; mt++) {
                uint32_t a[4];
                ldsm4t(a, sb + SM_WO + row * 64 + (((mt * 2 + lchk) ^ ((row >> 1) & 3)) << 4));
                mma16816(acc[mt], a[0], a[1], a[2], a[3], (uint32_t)w[ks][0], (uint32_t)w[ks][1]);
            }
        }
        if (u < 14) {
            mbar_wait(sb + SM_BAR + (CH_W2 + (u >= 7)) * 8);
            TS(14);
            const int row = u * 16 + lrow;
#pragma unroll
            for (int mt = 0; mt < 2; mt++) {
                uint32_t a[4];
                ldsm4t(a, sb + SM_W2 + row * 64 + (((mt * 2 + lchk) ^ ((row >> 1) & 3)) << 4));
                mma16816(acc[mt], a[0], a[1], a[2], a[3], (uint32_t)w[2][0], (uint32_t)w[2][1]);
            }
        }
        __syncwarp();
        if (ft == 0) {
            const uint32_t rb = sb + SM_WO + u * 2048;
#pragma unroll
            for (int mt = 0; mt < 2; mt++) {
                sts_f1(rb + (mt * 16 + fg) * 4, acc[mt][0]);
                sts_f1(rb + 128 + (mt * 16 + fg) * 4, acc[mt][1]);
                sts_f1(rb + (mt * 16 + fg + 8) * 4, acc[mt][2]);
                sts_f1(rb + 128 + (mt * 16 + fg + 8) * 4, acc[mt][3]);
            }
        }
        bar_sync(2, NCW * 32);
        if (u != 0) return;
        float2 s = make_float2(0.f, 0.f);
#pragma unroll
        for (int w2 = 0; w2 < NCW; w2++) {
            float2 v = lds_f2(sb + SM_WO + w2 * 2048 + lane * 8);
            s.x += v.x; s.y += v.y;
        }
        if (r != 0) {
            st_ll2(&sc->px[(g16 * 8 + r) * 64 + lane * 2], __float_as_uint(s.x), __float_as_uint(s.y), tag);
            TS(15);
            return;
        }
        TS(15);
        unsigned long long v[7][2];
        const unsigned long long* src = &sc->px[(g16 * 8 + 1) * 64 + lane * 2];
        unsigned n = 0;
        bool ok;
        do {
            ok = true;
#pragma unroll
            for (int i = 0; i < 7; i++) ld_ll2(src + i * 64, v[i][0], v[i][1]);
#pragma unroll
            for (int i = 0; i < 7; i++) ok = ok && (uint32_t)(v[i][0] >> 32) == tag && (uint32_t)(v[i][1] >> 32) == tag;
        } while (!ok && ++n < SPIN_LIMIT);
#pragma unroll
        for (int i = 0; i < 7; i++) { s.x += __uint_as_float((uint32_t)v[i][0]); s.y += __uint_as_float((uint32_t)v[i][1]); }
        reinterpret_cast<uint32_t*>(p.out)[(lane >> 4) * 256 + g16 * 16 + (lane & 15)] =
            pack_bf16(bf_lo(xres) + s.x, bf_hi(xres) + s.y);
        __syncwarp();
        if (c == 0 && lane == 0) sc->epoch = tag;
        TS(16);
    }
}

typedef CUresult (*EncodeTiledFn)(CUtensorMap*, CUtensorMapDataType, cuuint32_t, void*, const cuuint64_t*, const cuuint64_t*,
                                  const cuuint32_t*, const cuuint32_t*, CUtensorMapInterleave, CUtensorMapSwizzle,
                                  CUtensorMapL2promotion, CUtensorMapFloatOOBfill);

void make_map(EncodeTiledFn enc, CUtensorMap* m, const void* base, uint64_t cols, uint64_t rows, uint32_t box_c, uint32_t box_r,
              CUtensorMapSwizzle sw) {
    cuuint64_t gd[2] = {cols, rows};
    cuuint64_t gs[1] = {cols * 2};
    cuuint32_t bd[2] = {box_c, box_r};
    cuuint32_t es[2] = {1, 1};
    enc(m, CU_TENSOR_MAP_DATA_TYPE_BFLOAT16, 2, const_cast<void*>(base), gd, gs, bd, es, CU_TENSOR_MAP_INTERLEAVE_NONE, sw,
        CU_TENSOR_MAP_L2_PROMOTION_L2_128B, CU_TENSOR_MAP_FLOAT_OOB_FILL_NONE);
}

}

extern "C" void kernel_launch(void* const* d_in, const int* in_sizes, int n_in, void* d_out, int out_size) {
    (void)in_sizes; (void)n_in; (void)out_size;
    static EncodeTiledFn enc = nullptr;
    static Scratch* sc = nullptr;
    if (!enc) {
        void* fn = nullptr;
        cudaDriverEntryPointQueryResult st;
        cudaGetDriverEntryPoint("cuTensorMapEncodeTiled", &fn, cudaEnableDefault, &st);
        enc = (EncodeTiledFn)fn;
        cudaFuncSetAttribute(fused_decode_kernel, cudaFuncAttributeMaxDynamicSharedMemorySize, SM_TOTAL);
        void* sp = nullptr;
        cudaGetSymbolAddress(&sp, g_scratch);
        sc = (Scratch*)sp;
    }
    Params p;
    make_map(enc, &p.k, d_in[1], 128, 2 * 8 * SK, 64, 32, CU_TENSOR_MAP_SWIZZLE_128B);
    make_map(enc, &p.v, d_in[2], 128, 2 * 8 * SK, 16, 256, CU_TENSOR_MAP_SWIZZLE_32B);
    make_map(enc, &p.wq, d_in[3], 4096, 512, 32, 128, CU_TENSOR_MAP_SWIZZLE_64B);
    make_map(enc, &p.wo, d_in[4], 512, 4096, 32, 128, CU_TENSOR_MAP_SWIZZLE_64B);
    make_map(enc, &p.w1, d_in[6], FF, 512, 16, 256, CU_TENSOR_MAP_SWIZZLE_32B);
    make_map(enc, &p.w2, d_in[8], 512, FF, 32, 112, CU_TENSOR_MAP_SWIZZLE_64B);
    p.x = (const __nv_bfloat16*)d_in[0];
    p.b1 = (const __nv_bfloat16*)d_in[7];
    p.out = (__nv_bfloat16*)d_out;
    p.sc = sc;
    fused_decode_kernel<<<NCTA, NTHREADS, SM_TOTAL, cudaStreamPerThread>>>(p);
}
```

```cpp
#include <cuda_runtime.h>
#include <cuda_bf16.h>
#include <cuda.h>
#include <stdint.h>

namespace {

constexpr int D_MODEL = 512;
constexpr int SK = 8192;
constexpr int WIN = 2048;
constexpr int WIN0 = SK - WIN;
constexpr int FF = 1792;

constexpr int NCTA = 128;
constexpr int NCW = 16;
constexpr int NTHREADS = (NCW + 2) * 32;

constexpr int SM_WQ = 0;
constexpr int SM_K = SM_WQ + 32768;
constexpr int SM_V = SM_K + 65536;
constexpr int SM_W1 = SM_V + 65536;
constexpr int SM_WO = SM_W1 + 16384;
constexpr int SM_W2 = SM_WO + 32768;
constexpr int SM_BAR = SM_W2 + 14336;
constexpr int SM_Q = SM_BAR + 256;
constexpr int SM_XN = SM_Q + 1024;
constexpr int SM_MAX = SM_XN + 2048;
constexpr int SM_SUM = SM_MAX + 256;
constexpr int SM_EPOCH = SM_SUM + 256;
constexpr int SM_TOTAL = SM_EPOCH + 16;
constexpr int SM_P = SM_WQ;

constexpr int CH_WQ = 0, CH_K = 4, CH_V = 12, CH_W1 = 20, CH_WO = 22, CH_W2 = 26, NCHUNK = 28;
#define WINDOW 4

constexpr unsigned SPIN_LIMIT = 1u << 22;

struct Scratch {
    unsigned epoch;
    unsigned pad[31];
    unsigned long long qx[2 * 32 * 64];
    unsigned long long stx[128 * 8];
    unsigned long long opx[128 * 8 * 64];
    unsigned long long ox[2 * 256 * 8];
    unsigned long long ax[2 * 112 * 8];
    unsigned long long px[16 * 8 * 64];
};

__device__ Scratch g_scratch;

struct Params {
    CUtensorMap wq, k, v, w1, wo, w2;
    const __nv_bfloat16* x;
    const __nv_bfloat16* b1;
    __nv_bfloat16* out;
    Scratch* sc;
};

__device__ __forceinline__ uint32_t smem_u32(const void* p) { return (uint32_t)__cvta_generic_to_shared(p); }
__device__ __forceinline__ void mbar_init(uint32_t bar, uint32_t cnt) {
    asm volatile("mbarrier.init.shared::cta.b64 [%0], %1;" ::"r"(bar), "r"(cnt) : "memory");
}
__device__ __forceinline__ void mbar_expect_tx(uint32_t bar, uint32_t bytes) {
    asm volatile("mbarrier.arrive.expect_tx.shared::cta.b64 _, [%0], %1;" ::"r"(bar), "r"(bytes) : "memory");
}
__device__ __forceinline__ void mbar_wait(uint32_t bar) {
    unsigned n = 0;
    uint32_t ok;
    do {
        asm volatile("{\n.reg .pred p;\nmbarrier.try_wait.parity.shared::cta.b64 p, [%1], 0;\nselp.u32 %0, 1, 0, p;\n}"
                     : "=r"(ok) : "r"(bar) : "memory");
    } while (!ok && ++n < SPIN_LIMIT);
}
__device__ __forceinline__ void tma2d(uint32_t dst, const CUtensorMap* tm, int c0, int c1, uint32_t bar) {
    asm volatile("cp.async.bulk.tensor.2d.shared::cluster.global.mbarrier::complete_tx::bytes [%0], [%1, {%3, %4}], [%2];"
                 ::"r"(dst), "l"((uint64_t)tm), "r"(bar), "r"(c0), "r"(c1) : "memory");
}
__device__ __forceinline__ void bar_sync(int id, int n) { asm volatile("bar.sync %0, %1;" ::"r"(id), "r"(n) : "memory"); }
__device__ __forceinline__ void bar_arrive(int id, int n) { asm volatile("bar.arrive %0, %1;" ::"r"(id), "r"(n) : "memory"); }

__device__ __forceinline__ void ldsm4(uint32_t (&r)[4], uint32_t addr) {
    asm volatile("ldmatrix.sync.aligned.m8n8.x4.shared.b16 {%0,%1,%2,%3}, [%4];"
                 : "=r"(r[0]), "=r"(r[1]), "=r"(r[2]), "=r"(r[3]) : "r"(addr) : "memory");
}
__device__ __forceinline__ void ldsm4t(uint32_t (&r)[4], uint32_t addr) {
    asm volatile("ldmatrix.sync.aligned.m8n8.x4.trans.shared.b16 {%0,%1,%2,%3}, [%4];"
                 : "=r"(r[0]), "=r"(r[1]), "=r"(r[2]), "=r"(r[3]) : "r"(addr) : "memory");
}
__device__ __forceinline__ void mma16816(float (&c)[4], uint32_t a0, uint32_t a1, uint32_t a2, uint32_t a3, uint32_t b0, uint32_t b1) {
    asm volatile("mma.sync.aligned.m16n8k16.row.col.f32.bf16.bf16.f32 {%0,%1,%2,%3}, {%4,%5,%6,%7}, {%8,%9}, {%0,%1,%2,%3};"
                 : "+f"(c[0]), "+f"(c[1]), "+f"(c[2]), "+f"(c[3])
                 : "r"(a0), "r"(a1), "r"(a2), "r"(a3), "r"(b0), "r"(b1));
}
__device__ __forceinline__ void st_ll1(unsigned long long* p, uint32_t d, uint32_t tag) {
    unsigned long long w = ((unsigned long long)tag << 32) | d;
    asm volatile("st.relaxed.gpu.global.b64 [%0], %1;" ::"l"(p), "l"(w) : "memory");
}
__device__ __forceinline__ void st_ll2(unsigned long long* p, uint32_t d0, uint32_t d1, uint32_t tag) {
    unsigned long long w0 = ((unsigned long long)tag << 32) | d0, w1 = ((unsigned long long)tag << 32) | d1;
    asm volatile("st.relaxed.gpu.global.v2.b64 [%0], {%1, %2};" ::"l"(p), "l"(w0), "l"(w1) : "memory");
}
__device__ __forceinline__ void ld_ll2(const unsigned long long* p, unsigned long long& w0, unsigned long long& w1) {
    asm volatile("ld.relaxed.gpu.global.v2.b64 {%0, %1}, [%2];" : "=l"(w0), "=l"(w1) : "l"(p) : "memory");
}
__device__ __forceinline__ bool tag_ok(unsigned long long w0, unsigned long long w1, uint32_t tag) {
    return (uint32_t)(w0 >> 32) == tag && (uint32_t)(w1 >> 32) == tag;
}
__device__ __forceinline__ float ex2(float x) {
    float y;
    asm("ex2.approx.ftz.f32 %0, %1;" : "=f"(y) : "f"(x));
    return y;
}
__device__ __forceinline__ float bf16r(float x) { return __bfloat162float(__float2bfloat16_rn(x)); }
__device__ __forceinline__ uint32_t pack_bf16(float lo, float hi) {
    __nv_bfloat162 v = __floats2bfloat162_rn(lo, hi);
    return *reinterpret_cast<uint32_t*>(&v);
}
__device__ __forceinline__ float bf_lo(uint32_t u) { return __uint_as_float(u << 16); }
__device__ __forceinline__ float bf_hi(uint32_t u) { return __uint_as_float(u & 0xffff0000u); }
__device__ __forceinline__ float2 lds_f2(uint32_t a) {
    float2 v;
    asm volatile("ld.shared.v2.f32 {%0, %1}, [%2];" : "=f"(v.x), "=f"(v.y) : "r"(a) : "memory");
    return v;
}
__device__ __forceinline__ float lds_f1(uint32_t a) {
    float v;
    asm volatile("ld.shared.f32 %0, [%1];" : "=f"(v) : "r"(a) : "memory");
    return v;
}
__device__ __forceinline__ uint32_t lds_u1(uint32_t a) {
    uint32_t v;
    asm volatile("ld.shared.u32 %0, [%1];" : "=r"(v) : "r"(a) : "memory");
    return v;
}
__device__ __forceinline__ void sts_f1(uint32_t a, float v) { asm volatile("st.shared.f32 [%0], %1;" ::"r"(a), "f"(v) : "memory"); }
__device__ __forceinline__ void sts_u1(uint32_t a, uint32_t v) { asm volatile("st.shared.u32 [%0], %1;" ::"r"(a), "r"(v) : "memory"); }
__device__ __forceinline__ void sts_f2(uint32_t a, float x, float y) {
    asm volatile("st.shared.v2.f32 [%0], {%1, %2};" ::"r"(a), "f"(x), "f"(y) : "memory");
}

#define TS(i) do { } while (0)

__global__ void __launch_bounds__(NTHREADS, 1) fused_decode_kernel(const __grid_constant__ Params p) {
    extern __shared__ __align__(1024) uint8_t smem[];
    const uint32_t sb = smem_u32(smem);
    const int c = blockIdx.x;
    const int warp = threadIdx.x >> 5, lane = threadIdx.x & 31;
    const int bh = c >> 3, j = c & 7;
    const int r = c >> 4, g16 = c & 15;

    if (warp == NCW) {
        if (lane == 0) {
#pragma unroll
            for (int i = 0; i < 4; i++) mbar_init(sb + SM_BAR + i * 8, 1);
            asm volatile("fence.proxy.async.shared::cta;" ::: "memory");
#pragma unroll
            for (int i = 0; i < CH_K; i++) {
                mbar_expect_tx(sb + SM_BAR + i * 8, 8192);
                tma2d(sb + SM_WQ + i * 8192, &p.wq, 32 * c, 128 * i, sb + SM_BAR + i * 8);
                TS(i);
            }
#pragma unroll
            for (int k = 4; k < NCHUNK; k++) mbar_init(sb + SM_BAR + k * 8, 1);
            asm volatile("fence.proxy.async.shared::cta;" ::: "memory");
        }
        __syncwarp();
        bar_arrive(1, NTHREADS);
        if (lane == 0) {
            const int krow = bh * SK + WIN0;
#pragma unroll
            for (int i = CH_K; i < NCHUNK; i++) {
                const uint32_t bar = sb + SM_BAR + i * 8;
                if (i >= WINDOW) mbar_wait(bar - WINDOW * 8);
                if (i < CH_V) {
                    const int q = i - CH_K;
                    mbar_expect_tx(bar, 8192);
                    tma2d(sb + SM_K + q * 8192, &p.k, 0, krow + j * 256 + q * 32, bar);
                    tma2d(sb + SM_K + q * 8192 + 4096, &p.k, 64, krow + j * 256 + q * 32, bar);
                } else if (i < CH_W1) {
                    const int q = i - CH_V;
                    mbar_expect_tx(bar, 8192);
                    tma2d(sb + SM_V + q * 8192, &p.v, 0, krow + j * 256 + q * 32, bar);
                    tma2d(sb + SM_V + q * 8192 + 4096, &p.v, 64, krow + j * 256 + q * 32, bar);
                } else if (i < CH_WO) {
                    const int q = i - CH_W1;
                    if (c < 112) {
                        mbar_expect_tx(bar, 8192);
                        tma2d(sb + SM_W1 + q * 8192, &p.w1, 16 * c, 256 * q, bar);
                    } else {
                        mbar_expect_tx(bar, 0);
                    }
                } else if (i < CH_W2) {
                    const int q = i - CH_WO;
                    mbar_expect_tx(bar, 8192);
                    tma2d(sb + SM_WO + q * 8192, &p.wo, 32 * g16, 512 * r + 128 * q, bar);
                } else {
                    const int q = i - CH_W2;
                    mbar_expect_tx(bar, 7168);
                    tma2d(sb + SM_W2 + q * 7168, &p.w2, 32 * g16, 224 * r + 112 * q, bar);
                }
                TS(i);
            }
        }
        return;
    }
    if (warp == NCW + 1) {
        Scratch* const sc = p.sc;
        const uint32_t tag = *reinterpret_cast<volatile unsigned*>(&sc->epoch) + 1u;
        if (lane == 0) sts_u1(sb + SM_EPOCH, tag);
        __syncwarp();
        bar_arrive(1, NTHREADS);
        TS(0);
        const unsigned long long* src = &sc->qx[((bh >> 3) * 32 + (bh & 7) * 4) * 64 + 2 * lane];
        unsigned pend = 0xf, n = 0;
        while (true) {
            unsigned long long w[4][2];
#pragma unroll
            for (int h = 0; h < 4; h++)
                if (pend >> h & 1) ld_ll2(src + h * 64, w[h][0], w[h][1]);
#pragma unroll
            for (int h = 0; h < 4; h++)
                if ((pend >> h & 1) && tag_ok(w[h][0], w[h][1], tag)) {
                    const uint32_t dst = sb + SM_Q + ((h * 4 + ((2 * lane) & 3)) * 16 + (lane >> 1)) * 4;
                    sts_u1(dst, (uint32_t)w[h][0]);
                    sts_u1(dst + 64, (uint32_t)w[h][1]);
                    pend &= ~(1u << h);
                }
            if (__all_sync(~0u, pend == 0) || ++n >= SPIN_LIMIT) break;
            __nanosleep(100);
        }
        bar_arrive(3, NCW * 32 + 32);
        TS(1);
        const float LOG2E = 1.4426950408889634f;
        bar_sync(4, NCW * 32 + 32);
        {
            const int head = lane & 3, w0 = lane >> 2;
            float mx = fmaxf(lds_f1(sb + SM_MAX + (w0 * 4 + head) * 4), lds_f1(sb + SM_MAX + ((w0 + 8) * 4 + head) * 4));
            float sm = lds_f1(sb + SM_SUM + (w0 * 4 + head) * 4) + lds_f1(sb + SM_SUM + ((w0 + 8) * 4 + head) * 4);
#pragma unroll
            for (int o = 4; o < 32; o <<= 1) { mx = fmaxf(mx, __shfl_xor_sync(~0u, mx, o)); sm += __shfl_xor_sync(~0u, sm, o); }
            if (lane < 4) st_ll2(&sc->stx[(c * 4 + lane) * 2], __float_as_uint(mx), __float_as_uint(sm), tag);
        }
        TS(2);
        float coef[8];
        {
            unsigned long long w0, w1;
            const unsigned long long* sp = &sc->stx[(bh * 32 + lane) * 2];
            n = 0;
            while (true) {
                ld_ll2(sp, w0, w1);
                if (__all_sync(~0u, tag_ok(w0, w1, tag)) || ++n >= SPIN_LIMIT) break;
                __nanosleep(100);
            }
            const float mj = __uint_as_float((uint32_t)w0), lj = __uint_as_float((uint32_t)w1);
            float gm = mj;
#pragma unroll
            for (int o = 4; o < 32; o <<= 1) gm = fmaxf(gm, __shfl_xor_sync(~0u, gm, o));
            const float wj = ex2((mj - gm) * LOG2E);
            float gl = wj * lj;
#pragma unroll
            for (int o = 4; o < 32; o <<= 1) gl += __shfl_xor_sync(~0u, gl, o);
            const float cj = wj / gl;
#pragma unroll
            for (int k = 0; k < 8; k++) coef[k] = __shfl_sync(~0u, cj, k * 4 + (lane >> 3));
        }
        TS(3);
        mbar_wait(sb + SM_BAR + (CH_V + 7) * 8);
        {
            const unsigned long long* sp = &sc->opx[c * 512 + lane * 2];
            unsigned long long w[8][2];
            pend = 0xff; n = 0;
            while (true) {
#pragma unroll
                for (int k = 0; k < 8; k++)
                    if (pend >> k & 1) ld_ll2(sp + k * 64, w[k][0], w[k][1]);
#pragma unroll
                for (int k = 0; k < 8; k++)
                    if ((pend >> k & 1) && tag_ok(w[k][0], w[k][1], tag)) pend &= ~(1u << k);
                if (__all_sync(~0u, pend == 0) || ++n >= SPIN_LIMIT) break;
            }
            float o0 = 0.f, o1 = 0.f;
#pragma unroll
            for (int k = 0; k < 8; k++) {
                o0 = fmaf(coef[k], __uint_as_float((uint32_t)w[k][0]), o0);
                o1 = fmaf(coef[k], __uint_as_float((uint32_t)w[k][1]), o1);
            }
            const int head = (bh & 7) * 4 + (lane >> 3);
            st_ll1(&sc->ox[(((bh >> 3) * 256 + head * 8 + j) * 4 + (lane & 3)) * 2 + ((lane >> 2) & 1)], pack_bf16(o0, o1), tag);
        }
        TS(4);
        return;
    }

    const int u = warp;
    const int fg = lane >> 2, ft = lane & 3;
    Scratch* const sc = p.sc;

    uint32_t xres = 0;
    uint32_t b1pair = 0;
    if (u < 2) {
        const uint4* x4 = reinterpret_cast<const uint4*>(p.x) + u * 64 + lane * 2;
        const uint4 v0 = __ldg(x4), v1 = __ldg(x4 + 1);
        if (u == 0) xres = __ldg(reinterpret_cast<const uint32_t*>(p.x) + (lane >> 4) * 256 + g16 * 16 + (lane & 15));
        if (u == 1 && c < 112) b1pair = __ldg(reinterpret_cast<const uint32_t*>(p.b1) + c * 8 + (lane & 7));
        const uint32_t a[8] = {v0.x, v0.y, v0.z, v0.w, v1.x, v1.y, v1.z, v1.w};
        float s0 = 0.f;
#pragma unroll
        for (int i = 0; i < 8; i++) s0 += bf_lo(a[i]) + bf_hi(a[i]);
#pragma unroll
        for (int o = 16; o > 0; o >>= 1) s0 += __shfl_xor_sync(~0u, s0, o);
        const float m0 = s0 * (1.f / D_MODEL);
        float q0 = 0.f;
#pragma unroll
        for (int i = 0; i < 8; i++) {
            float d;
            d = bf_lo(a[i]) - m0; q0 += d * d; d = bf_hi(a[i]) - m0; q0 += d * d;
        }
#pragma unroll
        for (int o = 16; o > 0; o >>= 1) q0 += __shfl_xor_sync(~0u, q0, o);
        const float mean = bf16r(m0);
        const float var = bf16r(q0 * (1.f / D_MODEL));
        const float den = bf16r(sqrtf(bf16r(var + 1e-5f)));
        uint32_t o[8];
#pragma unroll
        for (int i = 0; i < 8; i++) o[i] = pack_bf16(bf16r(bf_lo(a[i]) - mean) / den, bf16r(bf_hi(a[i]) - mean) / den);
        const uint32_t dst = sb + SM_XN + u * 1024 + lane * 32;
        asm volatile("st.shared.v4.u32 [%0], {%1,%2,%3,%4};" ::"r"(dst), "r"(o[0]), "r"(o[1]), "r"(o[2]), "r"(o[3]) : "memory");
        asm volatile("st.shared.v4.u32 [%0], {%1,%2,%3,%4};" ::"r"(dst + 16), "r"(o[4]), "r"(o[5]), "r"(o[6]), "r"(o[7]) : "memory");
        TS(0);
    }

    const int lrow = (lane & 7) + ((lane >> 4) << 3);
    const int lchk = (lane >> 3) & 1;

    bar_sync(1, NTHREADS);
    const uint32_t tag = lds_u1(sb + SM_EPOCH);
    uint32_t xb[4];
#pragma unroll
    for (int i = 0; i < 4; i++) xb[i] = lds_u1(sb + SM_XN + (fg & 1) * 1024 + (u * 16 + i * 4 + ft) * 4);
    {
        mbar_wait(sb + SM_BAR + (CH_WQ + (u >> 2)) * 8);
        TS(1);
        float acc[2][4] = {};
#pragma unroll
        for (int ks = 0; ks < 2; ks++) {
            const int row = u * 32 + ks * 16 + lrow;
#pragma unroll
            for (int mt = 0; mt < 2; mt++) {
                uint32_t a[4];
                ldsm4t(a, sb + SM_WQ + row * 64 + (((mt * 2 + lchk) ^ ((row >> 1) & 3)) << 4));
                mma16816(acc[mt], a[0], a[1], a[2], a[3], xb[ks * 2], xb[ks * 2 + 1]);
            }
        }
        __syncwarp();
        if (ft == 0) {
            const uint32_t rb = sb + SM_WQ + u * 2048;
#pragma unroll
            for (int mt = 0; mt < 2; mt++) {
                sts_f1(rb + (mt * 16 + fg) * 4, acc[mt][0]);
                sts_f1(rb + 128 + (mt * 16 + fg) * 4, acc[mt][1]);
                sts_f1(rb + (mt * 16 + fg + 8) * 4, acc[mt][2]);
                sts_f1(rb + 128 + (mt * 16 + fg + 8) * 4, acc[mt][3]);
            }
        }
    }
    bar_sync(2, NCW * 32);
    if (u == 0) {
        float2 s = make_float2(0.f, 0.f);
#pragma unroll
        for (int w = 0; w < NCW; w++) {
            float2 v = lds_f2(sb + SM_WQ + w * 2048 + lane * 8);
            s.x += v.x; s.y += v.y;
        }
        st_ll1(&sc->qx[((lane >> 4) * 32 + (c >> 2)) * 64 + (c & 3) * 16 + (lane & 15)], pack_bf16(s.x, s.y), tag);
        TS(2);
    }
    bar_sync(3, NCW * 32 + 32);
    TS(3);

    {
        uint32_t qa[16];
        if (fg < 4) {
#pragma unroll
            for (int i = 0; i < 4; i++)
                asm volatile("ld.shared.v4.u32 {%0,%1,%2,%3}, [%4];"
                             : "=r"(qa[4 * i]), "=r"(qa[4 * i + 1]), "=r"(qa[4 * i + 2]), "=r"(qa[4 * i + 3])
                             : "r"(sb + SM_Q + (fg * 4 + ft) * 64 + i * 16) : "memory");
        } else {
#pragma unroll
            for (int i = 0; i < 16; i++) qa[i] = 0u;
        }
        mbar_wait(sb + SM_BAR + (CH_K + (u >> 1)) * 8);
        TS(4);
        float acc[2][4] = {};
        const uint32_t kb = sb + SM_K + (u >> 1) * 8192;
#pragma unroll
        for (int nt = 0; nt < 2; nt++) {
            const int row = (u & 1) * 16 + nt * 8 + (lane & 7);
#pragma unroll
            for (int q = 0; q < 4; q++) {
                const int chunk = q * 4 + (lane >> 3);
                uint32_t b[4];
                ldsm4(b, kb + (chunk >> 3) * 4096 + row * 128 + (((chunk & 7) ^ (row & 7)) << 4));
                mma16816(acc[nt], qa[4 * q], 0u, qa[4 * q + 1], 0u, b[0], b[1]);
                mma16816(acc[nt], qa[4 * q + 2], 0u, qa[4 * q + 3], 0u, b[2], b[3]);
            }
        }
        const float scale = 0.08838834764831845f;
        const float LOG2E = 1.4426950408889634f;
        float sv[4];
#pragma unroll
        for (int i = 0; i < 4; i++) sv[i] = bf16r(bf16r(acc[i >> 1][i & 1]) * scale);
        float m = fmaxf(fmaxf(sv[0], sv[1]), fmaxf(sv[2], sv[3]));
        m = fmaxf(m, __shfl_xor_sync(~0u, m, 1));
        m = fmaxf(m, __shfl_xor_sync(~0u, m, 2));
        if (lane < 16 && ft == 0) sts_f1(sb + SM_MAX + (u * 4 + fg) * 4, m);
        TS(5);
        bar_sync(2, NCW * 32);
        {
            const int head = fg & 3, e0 = ft + 4 * (fg >> 2);
            m = fmaxf(lds_f1(sb + SM_MAX + (e0 * 4 + head) * 4), lds_f1(sb + SM_MAX + ((e0 + 8) * 4 + head) * 4));
            m = fmaxf(m, __shfl_xor_sync(~0u, m, 1));
            m = fmaxf(m, __shfl_xor_sync(~0u, m, 2));
            m = fmaxf(m, __shfl_xor_sync(~0u, m, 16));
        }
#pragma unroll
        for (int i = 0; i < 4; i++) sv[i] = ex2((sv[i] - m) * LOG2E);
        float l = (sv[0] + sv[1]) + (sv[2] + sv[3]);
        l += __shfl_xor_sync(~0u, l, 1);
        l += __shfl_xor_sync(~0u, l, 2);
        if (lane < 16) {
            const uint32_t p0 = pack_bf16(sv[0], sv[1]), p1 = pack_bf16(sv[2], sv[3]);
            asm volatile("st.shared.v2.u32 [%0], {%1,%2};" ::"r"(sb + SM_P + ((u >> 1) * 16 + lane) * 16 + (u & 1) * 8), "r"(p0), "r"(p1) : "memory");
            if (ft == 0) sts_f1(sb + SM_SUM + (u * 4 + fg) * 4, l);
        }
        bar_sync(4, NCW * 32 + 32);
        TS(6);
    }

    unsigned long long wo_[3][2] = {};
    const unsigned long long* so = &sc->ox[((fg * 256 + r * 32 + u * 2) * 4 + ft) * 2];
    const unsigned long long* sa = &sc->ax[((fg * 112 + r * 14 + (u < 14 ? u : 0)) * 4 + ft) * 2];
    {
        uint32_t pa[8][4];
#pragma unroll
        for (int i = 0; i < 8; i++)
            asm volatile("ld.shared.v4.u32 {%0,%1,%2,%3}, [%4];"
                         : "=r"(pa[i][0]), "=r"(pa[i][1]), "=r"(pa[i][2]), "=r"(pa[i][3])
                         : "r"(sb + SM_P + (i * 16 + (lane & 15)) * 16) : "memory");
        float acc0[4] = {}, acc1[4] = {};
        const uint32_t vb = sb + SM_V + (u >> 3) * 4096 + lane * 128 + (((u & 7) ^ (lane & 7)) << 4);
#pragma unroll
        for (int i = 0; i < 8; i++) {
            mbar_wait(sb + SM_BAR + (CH_V + i) * 8);
            uint32_t b[4];
            ldsm4t(b, vb + i * 8192);
            mma16816(acc0, pa[i][0], 0u, pa[i][1], 0u, b[0], b[1]);
            mma16816(acc1, pa[i][2], 0u, pa[i][3], 0u, b[2], b[3]);
        }
        TS(8);
        if (lane < 16)
            st_ll2(&sc->opx[((bh * 8 + (u >> 1)) * 8 + j) * 64 + (fg * 8 + (u & 1) * 4 + ft) * 2],
                   __float_as_uint(acc0[0] + acc1[0]), __float_as_uint(acc0[1] + acc1[1]), tag);
        TS(9);
    }

    if (c < 112) {
        mbar_wait(sb + SM_BAR + (CH_W1 + (u >> 3)) * 8);
        TS(10);
        float acc[4] = {};
#pragma unroll
        for (int ks = 0; ks < 2; ks++) {
            const int row = u * 32 + ks * 16 + lrow;
            uint32_t a[4];
            ldsm4t(a, sb + SM_W1 + row * 32 + ((lchk ^ ((row >> 2) & 1)) << 4));
            mma16816(acc, a[0], a[1], a[2], a[3], xb[ks * 2], xb[ks * 2 + 1]);
        }
        __syncwarp();
        if (ft == 0) {
            const uint32_t rb = sb + SM_W1 + u * 1024;
            sts_f1(rb + fg * 4, acc[0]);
            sts_f1(rb + 64 + fg * 4, acc[1]);
            sts_f1(rb + (fg + 8) * 4, acc[2]);
            sts_f1(rb + 64 + (fg + 8) * 4, acc[3]);
        }
        bar_sync(2, NCW * 32);
        if (u == 1 && lane < 16) {
            float2 s = make_float2(0.f, 0.f);
#pragma unroll
            for (int w = 0; w < NCW; w++) {
                float2 v = lds_f2(sb + SM_W1 + w * 1024 + lane * 8);
                s.x += v.x; s.y += v.y;
            }
            float h[2] = {bf16r(bf16r(s.x) + bf_lo(b1pair)), bf16r(bf16r(s.y) + bf_hi(b1pair))};
            float a[2];
#pragma unroll
            for (int i = 0; i < 2; i++) {
                const float e = bf16r(__expf(-fabsf(h[i])));
                const float sp = bf16r(bf16r(log1pf(e)) + fmaxf(h[i], 0.f));
                a[i] = h[i] * bf16r(tanhf(sp));
            }
            const int dp = lane & 7;
            st_ll1(&sc->ax[(((lane >> 3) * 112 + c) * 4 + (dp & 3)) * 2 + (dp >> 2)], pack_bf16(a[0], a[1]), tag);
            TS(11);
        }
    }

    {
        unsigned long long (&w)[3][2] = wo_;
        if (lane < 8) {
            unsigned n = 0;
            while (true) {
                if (!tag_ok(w[0][0], w[0][1], tag)) ld_ll2(so, w[0][0], w[0][1]);
                if (!tag_ok(w[1][0], w[1][1], tag)) ld_ll2(so + 8, w[1][0], w[1][1]);
                if (!tag_ok(w[2][0], w[2][1], tag)) ld_ll2(sa, w[2][0], w[2][1]);
                if ((tag_ok(w[0][0], w[0][1], tag) && tag_ok(w[1][0], w[1][1], tag) && tag_ok(w[2][0], w[2][1], tag)) ||
                    ++n >= SPIN_LIMIT) break;
                __nanosleep(40);
            }
        }
        __syncwarp();
        TS(12);
        float acc[2][4] = {};
        mbar_wait(sb + SM_BAR + (CH_WO + (u >> 2)) * 8);
        TS(13);
#pragma unroll
        for (int ks = 0; ks < 2; ks++) {
            const int row = u * 32 + ks * 16 + lrow;
#pragma unroll
            for (int mt = 0; mt < 2; mt++) {
                uint32_t a[4];
                ldsm4t(a, sb + SM_WO + row * 64 + (((mt * 2 + lchk) ^ ((row >> 1) & 3)) << 4));
                mma16816(acc[mt], a[0], a[1], a[2], a[3], (uint32_t)w[ks][0], (uint32_t)w[ks][1]);
            }
        }
        if (u < 14) {
            mbar_wait(sb + SM_BAR + (CH_W2 + (u >= 7)) * 8);
            TS(14);
            const int row = u * 16 + lrow;
#pragma unroll
            for (int mt = 0; mt < 2; mt++) {
                uint32_t a[4];
                ldsm4t(a, sb + SM_W2 + row * 64 + (((mt * 2 + lchk) ^ ((row >> 1) & 3)) << 4));
                mma16816(acc[mt], a[0], a[1], a[2], a[3], (uint32_t)w[2][0], (uint32_t)w[2][1]);
            }
        }
        __syncwarp();
        if (ft == 0) {
            const uint32_t rb = sb + SM_WO + u * 2048;
#pragma unroll
            for (int mt = 0; mt < 2; mt++) {
                sts_f1(rb + (mt * 16 + fg) * 4, acc[mt][0]);
                sts_f1(rb + 128 + (mt * 16 + fg) * 4, acc[mt][1]);
                sts_f1(rb + (mt * 16 + fg + 8) * 4, acc[mt][2]);
                sts_f1(rb + 128 + (mt * 16 + fg + 8) * 4, acc[mt][3]);
            }
        }
        bar_sync(2, NCW * 32);
        if (u != 0) return;
        float2 s = make_float2(0.f, 0.f);
#pragma unroll
        for (int w2 = 0; w2 < NCW; w2++) {
            float2 v = lds_f2(sb + SM_WO + w2 * 2048 + lane * 8);
            s.x += v.x; s.y += v.y;
        }
        if (r != 0) {
            st_ll2(&sc->px[(g16 * 8 + r) * 64 + lane * 2], __float_as_uint(s.x), __float_as_uint(s.y), tag);
            TS(15);
            return;
        }
        TS(15);
        unsigned long long v[7][2];
        const unsigned long long* src = &sc->px[(g16 * 8 + 1) * 64 + lane * 2];
        unsigned n = 0;
        bool ok;
        do {
            ok = true;
#pragma unroll
            for (int i = 0; i < 7; i++) ld_ll2(src + i * 64, v[i][0], v[i][1]);
#pragma unroll
            for (int i = 0; i < 7; i++) ok = ok && (uint32_t)(v[i][0] >> 32) == tag && (uint32_t)(v[i][1] >> 32) == tag;
        } while (!ok && ++n < SPIN_LIMIT);
#pragma unroll
        for (int i = 0; i < 7; i++) { s.x += __uint_as_float((uint32_t)v[i][0]); s.y += __uint_as_float((uint32_t)v[i][1]); }
        reinterpret_cast<uint32_t*>(p.out)[(lane >> 4) * 256 + g16 * 16 + (lane & 15)] =
            pack_bf16(bf_lo(xres) + s.x, bf_hi(xres) + s.y);
        __syncwarp();
        if (c == 0 && lane == 0) sc->epoch = tag;
        TS(16);
    }
}

typedef CUresult (*EncodeTiledFn)(CUtensorMap*, CUtensorMapDataType, cuuint32_t, void*, const cuuint64_t*, const cuuint64_t*,
                                  const cuuint32_t*, const cuuint32_t*, CUtensorMapInterleave, CUtensorMapSwizzle,
                                  CUtensorMapL2promotion, CUtensorMapFloatOOBfill);

void make_map(EncodeTiledFn enc, CUtensorMap* m, const void* base, uint64_t cols, uint64_t rows, uint32_t box_c, uint32_t box_r,
              CUtensorMapSwizzle sw) {
    cuuint64_t gd[2] = {cols, rows};
    cuuint64_t gs[1] = {cols * 2};
    cuuint32_t bd[2] = {box_c, box_r};
    cuuint32_t es[2] = {1, 1};
    enc(m, CU_TENSOR_MAP_DATA_TYPE_BFLOAT16, 2, const_cast<void*>(base), gd, gs, bd, es, CU_TENSOR_MAP_INTERLEAVE_NONE, sw,
        CU_TENSOR_MAP_L2_PROMOTION_L2_128B, CU_TENSOR_MAP_FLOAT_OOB_FILL_NONE);
}

}

extern "C" void kernel_launch(void* const* d_in, const int* in_sizes, int n_in, void* d_out, int out_size) {
    (void)in_sizes; (void)n_in; (void)out_size;
    static EncodeTiledFn enc = nullptr;
    static Scratch* sc = nullptr;
    if (!enc) {
        void* fn = nullptr;
        cudaDriverEntryPointQueryResult st;
        cudaGetDriverEntryPoint("cuTensorMapEncodeTiled", &fn, cudaEnableDefault, &st);
        enc = (EncodeTiledFn)fn;
        cudaFuncSetAttribute(fused_decode_kernel, cudaFuncAttributeMaxDynamicSharedMemorySize, SM_TOTAL);
        void* sp = nullptr;
        cudaGetSymbolAddress(&sp, g_scratch);
        sc = (Scratch*)sp;
    }
    Params p;
    make_map(enc, &p.k, d_in[1], 128, 2 * 8 * SK, 64, 32, CU_TENSOR_MAP_SWIZZLE_128B);
    make_map(enc, &p.v, d_in[2], 128, 2 * 8 * SK, 64, 32, CU_TENSOR_MAP_SWIZZLE_128B);
    make_map(enc, &p.wq, d_in[3], 4096, 512, 32, 128, CU_TENSOR_MAP_SWIZZLE_64B);
    make_map(enc, &p.wo, d_in[4], 512, 4096, 32, 128, CU_TENSOR_MAP_SWIZZLE_64B);
    make_map(enc, &p.w1, d_in[6], FF, 512, 16, 256, CU_TENSOR_MAP_SWIZZLE_32B);
    make_map(enc, &p.w2, d_in[8], 512, FF, 32, 112, CU_TENSOR_MAP_SWIZZLE_64B);
    p.x = (const __nv_bfloat16*)d_in[0];
    p.b1 = (const __nv_bfloat16*)d_in[7];
    p.out = (__nv_bfloat16*)d_out;
    p.sc = sc;
    fused_decode_kernel<<<NCTA, NTHREADS, SM_TOTAL, cudaStreamPerThread>>>(p);
}
```

```cpp
#include <cuda_runtime.h>
#include <cuda_bf16.h>
#include <cuda.h>
#include <stdint.h>

namespace {

constexpr int D_MODEL = 512;
constexpr int SK = 8192;
constexpr int WIN = 2048;
constexpr int WIN0 = SK - WIN;
constexpr int FF = 1792;

constexpr int NCTA = 128;
constexpr int NCW = 16;
constexpr int NTHREADS = (NCW + 2) * 32;

constexpr int SM_WQ = 0;
constexpr int SM_K = SM_WQ + 32768;
constexpr int SM_V = SM_K + 65536;
constexpr int SM_W1 = SM_V + 65536;
constexpr int SM_WO = SM_W1 + 16384;
constexpr int SM_W2 = SM_WO + 32768;
constexpr int SM_BAR = SM_W2 + 14336;
constexpr int SM_Q = SM_BAR + 256;
constexpr int SM_XN = SM_Q + 1024;
constexpr int SM_STAT = SM_XN + 2048;
constexpr int SM_EPOCH = SM_STAT + 512;
constexpr int SM_TOTAL = SM_EPOCH + 16;

constexpr int CH_WQ = 0, CH_K = 4, CH_V = 12, CH_W1 = 20, CH_WO = 22, CH_W2 = 26, NCHUNK = 28;
#define WINDOW 4

#define GATHER_SLEEP 200
constexpr unsigned SPIN_LIMIT = 1u << 22;

struct Scratch {
    unsigned epoch;
    unsigned pad[31];
    unsigned long long qx[2 * 32 * 64];
    unsigned long long sx[16 * 128 * 32];
    unsigned long long ox[2 * 256 * 8];
    unsigned long long ax[2 * 112 * 8];
    unsigned long long px[16 * 8 * 64];
};

__device__ Scratch g_scratch;

struct Params {
    CUtensorMap wq, k, v, w1, wo, w2;
    const __nv_bfloat16* x;
    const __nv_bfloat16* b1;
    __nv_bfloat16* out;
    Scratch* sc;
};

__device__ __forceinline__ uint32_t smem_u32(const void* p) { return (uint32_t)__cvta_generic_to_shared(p); }
__device__ __forceinline__ void mbar_init(uint32_t bar, uint32_t cnt) {
    asm volatile("mbarrier.init.shared::cta.b64 [%0], %1;" ::"r"(bar), "r"(cnt) : "memory");
}
__device__ __forceinline__ void mbar_expect_tx(uint32_t bar, uint32_t bytes) {
    asm volatile("mbarrier.arrive.expect_tx.shared::cta.b64 _, [%0], %1;" ::"r"(bar), "r"(bytes) : "memory");
}
__device__ __forceinline__ void mbar_wait(uint32_t bar) {
    unsigned n = 0;
    uint32_t ok;
    do {
        asm volatile("{\n.reg .pred p;\nmbarrier.try_wait.parity.shared::cta.b64 p, [%1], 0;\nselp.u32 %0, 1, 0, p;\n}"
                     : "=r"(ok) : "r"(bar) : "memory");
    } while (!ok && ++n < SPIN_LIMIT);
}
__device__ __forceinline__ void tma2d(uint32_t dst, const CUtensorMap* tm, int c0, int c1, uint32_t bar) {
    asm volatile("cp.async.bulk.tensor.2d.shared::cluster.global.mbarrier::complete_tx::bytes [%0], [%1, {%3, %4}], [%2];"
                 ::"r"(dst), "l"((uint64_t)tm), "r"(bar), "r"(c0), "r"(c1) : "memory");
}
__device__ __forceinline__ void bar_sync(int id, int n) { asm volatile("bar.sync %0, %1;" ::"r"(id), "r"(n) : "memory"); }
__device__ __forceinline__ void bar_arrive(int id, int n) { asm volatile("bar.arrive %0, %1;" ::"r"(id), "r"(n) : "memory"); }

__device__ __forceinline__ void ldsm4(uint32_t (&r)[4], uint32_t addr) {
    asm volatile("ldmatrix.sync.aligned.m8n8.x4.shared.b16 {%0,%1,%2,%3}, [%4];"
                 : "=r"(r[0]), "=r"(r[1]), "=r"(r[2]), "=r"(r[3]) : "r"(addr) : "memory");
}
__device__ __forceinline__ void ldsm4t(uint32_t (&r)[4], uint32_t addr) {
    asm volatile("ldmatrix.sync.aligned.m8n8.x4.trans.shared.b16 {%0,%1,%2,%3}, [%4];"
                 : "=r"(r[0]), "=r"(r[1]), "=r"(r[2]), "=r"(r[3]) : "r"(addr) : "memory");
}
__device__ __forceinline__ void mma16816(float (&c)[4], uint32_t a0, uint32_t a1, uint32_t a2, uint32_t a3, uint32_t b0, uint32_t b1) {
    asm volatile("mma.sync.aligned.m16n8k16.row.col.f32.bf16.bf16.f32 {%0,%1,%2,%3}, {%4,%5,%6,%7}, {%8,%9}, {%0,%1,%2,%3};"
                 : "+f"(c[0]), "+f"(c[1]), "+f"(c[2]), "+f"(c[3])
                 : "r"(a0), "r"(a1), "r"(a2), "r"(a3), "r"(b0), "r"(b1));
}
__device__ __forceinline__ void st_ll1(unsigned long long* p, uint32_t d, uint32_t tag) {
    unsigned long long w = ((unsigned long long)tag << 32) | d;
    asm volatile("st.relaxed.gpu.global.b64 [%0], %1;" ::"l"(p), "l"(w) : "memory");
}
__device__ __forceinline__ void st_ll2(unsigned long long* p, uint32_t d0, uint32_t d1, uint32_t tag) {
    unsigned long long w0 = ((unsigned long long)tag << 32) | d0, w1 = ((unsigned long long)tag << 32) | d1;
    asm volatile("st.relaxed.gpu.global.v2.b64 [%0], {%1, %2};" ::"l"(p), "l"(w0), "l"(w1) : "memory");
}
__device__ __forceinline__ void ld_ll2(const unsigned long long* p, unsigned long long& w0, unsigned long long& w1) {
    asm volatile("ld.relaxed.gpu.global.v2.b64 {%0, %1}, [%2];" : "=l"(w0), "=l"(w1) : "l"(p) : "memory");
}
__device__ __forceinline__ bool tag_ok(unsigned long long w0, unsigned long long w1, uint32_t tag) {
    return (uint32_t)(w0 >> 32) == tag && (uint32_t)(w1 >> 32) == tag;
}
__device__ __forceinline__ float ex2(float x) {
    float y;
    asm("ex2.approx.ftz.f32 %0, %1;" : "=f"(y) : "f"(x));
    return y;
}
__device__ __forceinline__ float bf16r(float x) { return __bfloat162float(__float2bfloat16_rn(x)); }
__device__ __forceinline__ uint32_t pack_bf16(float lo, float hi) {
    __nv_bfloat162 v = __floats2bfloat162_rn(lo, hi);
    return *reinterpret_cast<uint32_t*>(&v);
}
__device__ __forceinline__ float bf_lo(uint32_t u) { return __uint_as_float(u << 16); }
__device__ __forceinline__ float bf_hi(uint32_t u) { return __uint_as_float(u & 0xffff0000u); }
__device__ __forceinline__ float2 lds_f2(uint32_t a) {
    float2 v;
    asm volatile("ld.shared.v2.f32 {%0, %1}, [%2];" : "=f"(v.x), "=f"(v.y) : "r"(a) : "memory");
    return v;
}
__device__ __forceinline__ float lds_f1(uint32_t a) {
    float v;
    asm volatile("ld.shared.f32 %0, [%1];" : "=f"(v) : "r"(a) : "memory");
    return v;
}
__device__ __forceinline__ uint32_t lds_u1(uint32_t a) {
    uint32_t v;
    asm volatile("ld.shared.u32 %0, [%1];" : "=r"(v) : "r"(a) : "memory");
    return v;
}
__device__ __forceinline__ void sts_f1(uint32_t a, float v) { asm volatile("st.shared.f32 [%0], %1;" ::"r"(a), "f"(v) : "memory"); }
__device__ __forceinline__ void sts_u1(uint32_t a, uint32_t v) { asm volatile("st.shared.u32 [%0], %1;" ::"r"(a), "r"(v) : "memory"); }
__device__ __forceinline__ void sts_f2(uint32_t a, float x, float y) {
    asm volatile("st.shared.v2.f32 [%0], {%1, %2};" ::"r"(a), "f"(x), "f"(y) : "memory");
}

#define TS(i) do { } while (0)

__global__ void __launch_bounds__(NTHREADS, 1) fused_decode_kernel(const __grid_constant__ Params p) {
    extern __shared__ __align__(1024) uint8_t smem[];
    const uint32_t sb = smem_u32(smem);
    const int c = blockIdx.x;
    const int warp = threadIdx.x >> 5, lane = threadIdx.x & 31;
    const int bh = c >> 3, j = c & 7;
    const int r = c >> 4, g16 = c & 15;

    if (warp == NCW) {
        if (lane == 0) {
#pragma unroll
            for (int i = 0; i < 4; i++) mbar_init(sb + SM_BAR + i * 8, 1);
            asm volatile("fence.proxy.async.shared::cta;" ::: "memory");
#pragma unroll
            for (int i = 0; i < CH_K; i++) {
                mbar_expect_tx(sb + SM_BAR + i * 8, 8192);
                tma2d(sb + SM_WQ + i * 8192, &p.wq, 32 * c, 128 * i, sb + SM_BAR + i * 8);
                TS(i);
            }
#pragma unroll
            for (int k = 4; k < NCHUNK; k++) mbar_init(sb + SM_BAR + k * 8, 1);
            asm volatile("fence.proxy.async.shared::cta;" ::: "memory");
        }
        __syncwarp();
        bar_arrive(1, NTHREADS);
        if (lane == 0) {
            const int krow = bh * SK + WIN0;
#pragma unroll
            for (int i = CH_K; i < NCHUNK; i++) {
                const uint32_t bar = sb + SM_BAR + i * 8;
                if (i >= WINDOW) mbar_wait(bar - WINDOW * 8);
                if (i < CH_V) {
                    const int q = i - CH_K;
                    mbar_expect_tx(bar, 8192);
                    tma2d(sb + SM_K + q * 8192, &p.k, 0, krow + j * 256 + q * 32, bar);
                    tma2d(sb + SM_K + q * 8192 + 4096, &p.k, 64, krow + j * 256 + q * 32, bar);
                } else if (i < CH_W1) {
                    const int q = i - CH_V;
                    mbar_expect_tx(bar, 8192);
                    tma2d(sb + SM_V + q * 8192, &p.v, 16 * j, krow + q * 256, bar);
                } else if (i < CH_WO) {
                    const int q = i - CH_W1;
                    if (c < 112) {
                        mbar_expect_tx(bar, 8192);
                        tma2d(sb + SM_W1 + q * 8192, &p.w1, 16 * c, 256 * q, bar);
                    } else {
                        mbar_expect_tx(bar, 0);
                    }
                } else if (i < CH_W2) {
                    const int q = i - CH_WO;
                    mbar_expect_tx(bar, 8192);
                    tma2d(sb + SM_WO + q * 8192, &p.wo, 32 * g16, 512 * r + 128 * q, bar);
                } else {
                    const int q = i - CH_W2;
                    mbar_expect_tx(bar, 7168);
                    tma2d(sb + SM_W2 + q * 7168, &p.w2, 32 * g16, 224 * r + 112 * q, bar);
                }
                TS(i);
            }
        }
        return;
    }
    if (warp == NCW + 1) {
        Scratch* const sc = p.sc;
        const uint32_t tag = *reinterpret_cast<volatile unsigned*>(&sc->epoch) + 1u;
        if (lane == 0) sts_u1(sb + SM_EPOCH, tag);
        __syncwarp();
        bar_arrive(1, NTHREADS);
        TS(0);
        const unsigned long long* src = &sc->qx[((bh >> 3) * 32 + (bh & 7) * 4) * 64 + 2 * lane];
        unsigned pend = 0xf, n = 0;
        while (true) {
            unsigned long long w[4][2];
#pragma unroll
            for (int h = 0; h < 4; h++)
                if (pend >> h & 1) ld_ll2(src + h * 64, w[h][0], w[h][1]);
#pragma unroll
            for (int h = 0; h < 4; h++)
                if ((pend >> h & 1) && tag_ok(w[h][0], w[h][1], tag)) {
                    const uint32_t dst = sb + SM_Q + ((h * 4 + ((2 * lane) & 3)) * 16 + (lane >> 1)) * 4;
                    sts_u1(dst, (uint32_t)w[h][0]);
                    sts_u1(dst + 64, (uint32_t)w[h][1]);
                    pend &= ~(1u << h);
                }
            if (__all_sync(~0u, pend == 0) || ++n >= SPIN_LIMIT) break;
            __nanosleep(100);
        }
        bar_arrive(3, NCW * 32 + 32);
        TS(1);
        return;
    }

    const int u = warp;
    const int fg = lane >> 2, ft = lane & 3;
    Scratch* const sc = p.sc;

    uint32_t xres = 0;
    uint32_t b1pair = 0;
    if (u < 2) {
        const uint4* x4 = reinterpret_cast<const uint4*>(p.x) + u * 64 + lane * 2;
        const uint4 v0 = __ldg(x4), v1 = __ldg(x4 + 1);
        if (u == 0) xres = __ldg(reinterpret_cast<const uint32_t*>(p.x) + (lane >> 4) * 256 + g16 * 16 + (lane & 15));
        if (u == 1 && c < 112) b1pair = __ldg(reinterpret_cast<const uint32_t*>(p.b1) + c * 8 + (lane & 7));
        const uint32_t a[8] = {v0.x, v0.y, v0.z, v0.w, v1.x, v1.y, v1.z, v1.w};
        float s0 = 0.f;
#pragma unroll
        for (int i = 0; i < 8; i++) s0 += bf_lo(a[i]) + bf_hi(a[i]);
#pragma unroll
        for (int o = 16; o > 0; o >>= 1) s0 += __shfl_xor_sync(~0u, s0, o);
        const float m0 = s0 * (1.f / D_MODEL);
        float q0 = 0.f;
#pragma unroll
        for (int i = 0; i < 8; i++) {
            float d;
            d = bf_lo(a[i]) - m0; q0 += d * d; d = bf_hi(a[i]) - m0; q0 += d * d;
        }
#pragma unroll
        for (int o = 16; o > 0; o >>= 1) q0 += __shfl_xor_sync(~0u, q0, o);
        const float mean = bf16r(m0);
        const float var = bf16r(q0 * (1.f / D_MODEL));
        const float den = bf16r(sqrtf(bf16r(var + 1e-5f)));
        uint32_t o[8];
#pragma unroll
        for (int i = 0; i < 8; i++) o[i] = pack_bf16(bf16r(bf_lo(a[i]) - mean) / den, bf16r(bf_hi(a[i]) - mean) / den);
        const uint32_t dst = sb + SM_XN + u * 1024 + lane * 32;
        asm volatile("st.shared.v4.u32 [%0], {%1,%2,%3,%4};" ::"r"(dst), "r"(o[0]), "r"(o[1]), "r"(o[2]), "r"(o[3]) : "memory");
        asm volatile("st.shared.v4.u32 [%0], {%1,%2,%3,%4};" ::"r"(dst + 16), "r"(o[4]), "r"(o[5]), "r"(o[6]), "r"(o[7]) : "memory");
        TS(0);
    }

    const int lrow = (lane & 7) + ((lane >> 4) << 3);
    const int lchk = (lane >> 3) & 1;

    bar_sync(1, NTHREADS);
    const uint32_t tag = lds_u1(sb + SM_EPOCH);
    uint32_t xb[4];
#pragma unroll
    for (int i = 0; i < 4; i++) xb[i] = lds_u1(sb + SM_XN + (fg & 1) * 1024 + (u * 16 + i * 4 + ft) * 4);
    {
        mbar_wait(sb + SM_BAR + (CH_WQ + (u >> 2)) * 8);
        TS(1);
        float acc[2][4] = {};
#pragma unroll
        for (int ks = 0; ks < 2; ks++) {
            const int row = u * 32 + ks * 16 + lrow;
#pragma unroll
            for (int mt = 0; mt < 2; mt++) {
                uint32_t a[4];
                ldsm4t(a, sb + SM_WQ + row * 64 + (((mt * 2 + lchk) ^ ((row >> 1) & 3)) << 4));
                mma16816(acc[mt], a[0], a[1], a[2], a[3], xb[ks * 2], xb[ks * 2 + 1]);
            }
        }
        __syncwarp();
        if (ft == 0) {
            const uint32_t rb = sb + SM_WQ + u * 2048;
#pragma unroll
            for (int mt = 0; mt < 2; mt++) {
                sts_f1(rb + (mt * 16 + fg) * 4, acc[mt][0]);
                sts_f1(rb + 128 + (mt * 16 + fg) * 4, acc[mt][1]);
                sts_f1(rb + (mt * 16 + fg + 8) * 4, acc[mt][2]);
                sts_f1(rb + 128 + (mt * 16 + fg + 8) * 4, acc[mt][3]);
            }
        }
    }
    bar_sync(2, NCW * 32);
    if (u == 0) {
        float2 s = make_float2(0.f, 0.f);
#pragma unroll
        for (int w = 0; w < NCW; w++) {
            float2 v = lds_f2(sb + SM_WQ + w * 2048 + lane * 8);
            s.x += v.x; s.y += v.y;
        }
        st_ll1(&sc->qx[((lane >> 4) * 32 + (c >> 2)) * 64 + (c & 3) * 16 + (lane & 15)], pack_bf16(s.x, s.y), tag);
        TS(2);
    }
    bar_sync(3, NCW * 32 + 32);
    TS(3);

    {
        uint32_t qa[16];
        if (fg < 4) {
#pragma unroll
            for (int i = 0; i < 4; i++)
                asm volatile("ld.shared.v4.u32 {%0,%1,%2,%3}, [%4];"
                             : "=r"(qa[4 * i]), "=r"(qa[4 * i + 1]), "=r"(qa[4 * i + 2]), "=r"(qa[4 * i + 3])
                             : "r"(sb + SM_Q + (fg * 4 + ft) * 64 + i * 16) : "memory");
        } else {
#pragma unroll
            for (int i = 0; i < 16; i++) qa[i] = 0u;
        }
        mbar_wait(sb + SM_BAR + (CH_K + (u >> 1)) * 8);
        TS(4);
        float acc[2][4] = {};
        const uint32_t kb = sb + SM_K + (u >> 1) * 8192;
#pragma unroll
        for (int nt = 0; nt < 2; nt++) {
            const int row = (u & 1) * 16 + nt * 8 + (lane & 7);
#pragma unroll
            for (int q = 0; q < 4; q++) {
                const int chunk = q * 4 + (lane >> 3);
                uint32_t b[4];
                ldsm4(b, kb + (chunk >> 3) * 4096 + row * 128 + (((chunk & 7) ^ (row & 7)) << 4));
                mma16816(acc[nt], qa[4 * q], 0u, qa[4 * q + 1], 0u, b[0], b[1]);
                mma16816(acc[nt], qa[4 * q + 2], 0u, qa[4 * q + 3], 0u, b[2], b[3]);
            }
        }
        if (lane < 16) {
            const float scale = 0.08838834764831845f;
            const uint32_t d0 = pack_bf16(bf16r(acc[0][0]) * scale, bf16r(acc[0][1]) * scale);
            const uint32_t d1 = pack_bf16(bf16r(acc[1][0]) * scale, bf16r(acc[1][1]) * scale);
            st_ll2(&sc->sx[((bh * 128 + j * 16 + u) * 16 + lane) * 2], d0, d1, tag);
        }
        TS(5);
    }

    uint32_t pb[4][2];
    unsigned long long wo_[3][2] = {};
    const unsigned long long* so = &sc->ox[((fg * 256 + r * 32 + u * 2) * 4 + ft) * 2];
    const unsigned long long* sa = &sc->ax[((fg * 112 + r * 14 + (u < 14 ? u : 0)) * 4 + ft) * 2];
    {
        unsigned n = 0;
        unsigned long long w[4][2];
        const unsigned long long* src = &sc->sx[((bh * 128 + u * 8) * 16 + lane) * 2];
        unsigned pend = 0xf;
        while (true) {
#pragma unroll
            for (int i = 0; i < 4; i++)
                if (pend >> i & 1) ld_ll2(src + i * 64, w[i][0], w[i][1]);
#pragma unroll
            for (int i = 0; i < 4; i++)
                if ((pend >> i & 1) && tag_ok(w[i][0], w[i][1], tag)) pend &= ~(1u << i);
            if (__all_sync(~0u, pend == 0) || ++n >= SPIN_LIMIT) break;
            __nanosleep(GATHER_SLEEP);
        }
        __syncwarp();
        TS(6);
        float s[16];
#pragma unroll
        for (int i = 0; i < 4; i++) {
            s[4 * i] = bf_lo((uint32_t)w[i][0]); s[4 * i + 1] = bf_hi((uint32_t)w[i][0]);
            s[4 * i + 2] = bf_lo((uint32_t)w[i][1]); s[4 * i + 3] = bf_hi((uint32_t)w[i][1]);
        }
        float m = s[0];
#pragma unroll
        for (int i = 1; i < 16; i++) m = fmaxf(m, s[i]);
        m = fmaxf(m, __shfl_xor_sync(~0u, m, 1));
        m = fmaxf(m, __shfl_xor_sync(~0u, m, 2));
        m = fmaxf(m, __shfl_xor_sync(~0u, m, 16));
        const float LOG2E = 1.4426950408889634f;
        float l = 0.f;
#pragma unroll
        for (int i = 0; i < 16; i++) { s[i] = ex2((s[i] - m) * LOG2E); l += s[i]; }
        l += __shfl_xor_sync(~0u, l, 1);
        l += __shfl_xor_sync(~0u, l, 2);
        l += __shfl_xor_sync(~0u, l, 16);
        const int head = fg & 3;
        if (lane < 16 && ft == 0) sts_f2(sb + SM_STAT + (u * 4 + head) * 8, m, l);
        bar_sync(2, NCW * 32);
        const int e0 = ft + 4 * (fg >> 2);
        const float2 sa0 = lds_f2(sb + SM_STAT + (e0 * 4 + head) * 8), sa1 = lds_f2(sb + SM_STAT + ((e0 + 8) * 4 + head) * 8);
        float gm = fmaxf(sa0.x, sa1.x);
        gm = fmaxf(gm, __shfl_xor_sync(~0u, gm, 1));
        gm = fmaxf(gm, __shfl_xor_sync(~0u, gm, 2));
        gm = fmaxf(gm, __shfl_xor_sync(~0u, gm, 16));
        float gl = sa0.y * ex2((sa0.x - gm) * LOG2E) + sa1.y * ex2((sa1.x - gm) * LOG2E);
        gl += __shfl_xor_sync(~0u, gl, 1);
        gl += __shfl_xor_sync(~0u, gl, 2);
        gl += __shfl_xor_sync(~0u, gl, 16);
        const float f = __fdividef(ex2((m - gm) * LOG2E), gl);
#pragma unroll
        for (int i = 0; i < 4; i++) {
            pb[i][0] = pack_bf16(s[4 * i] * f, s[4 * i + 1] * f);
            pb[i][1] = pack_bf16(s[4 * i + 2] * f, s[4 * i + 3] * f);
        }
        TS(7);
    }

    {
        mbar_wait(sb + SM_BAR + (CH_V + (u >> 1)) * 8);
        TS(8);
        float accE[4] = {}, accO[4] = {};
#pragma unroll
        for (int i = 0; i < 4; i++) {
            uint32_t a[4], a2[4];
            const int row = u * 128 + i * 32 + lrow;
            const uint32_t addr = sb + SM_V + row * 32 + ((lchk ^ ((row >> 2) & 1)) << 4);
            ldsm4t(a, addr);
            ldsm4t(a2, addr + 512);
            mma16816(accE, a[0], a[1], a[2], a[3], pb[i][0], pb[i][1]);
            mma16816(accO, a2[0], a2[1], a2[2], a2[3], pb[i][0], pb[i][1]);
        }
#pragma unroll
        for (int i = 0; i < 4; i++) accE[i] += __shfl_xor_sync(~0u, accO[i], 2);
        __syncwarp();
        if (ft < 2) {
            const uint32_t rb = sb + SM_V + u * 4096;
            sts_f1(rb + ((2 * ft) * 16 + fg) * 4, accE[0]);
            sts_f1(rb + ((2 * ft + 1) * 16 + fg) * 4, accE[1]);
            sts_f1(rb + ((2 * ft) * 16 + fg + 8) * 4, accE[2]);
            sts_f1(rb + ((2 * ft + 1) * 16 + fg + 8) * 4, accE[3]);
        }
        bar_sync(2, NCW * 32);
        if (u == 0) {
            float2 s = make_float2(0.f, 0.f);
#pragma unroll
            for (int w = 0; w < NCW; w++) {
                float2 v = lds_f2(sb + SM_V + w * 4096 + lane * 8);
                s.x += v.x; s.y += v.y;
            }
            const int head = (bh & 7) * 4 + (lane >> 3), dp = lane & 7;
            st_ll1(&sc->ox[(((bh >> 3) * 256 + head * 8 + j) * 4 + (dp & 3)) * 2 + (dp >> 2)], pack_bf16(s.x, s.y), tag);
            TS(9);
        }
    }

    if (c < 112) {
        mbar_wait(sb + SM_BAR + (CH_W1 + (u >> 3)) * 8);
        TS(10);
        float acc[4] = {};
#pragma unroll
        for (int ks = 0; ks < 2; ks++) {
            const int row = u * 32 + ks * 16 + lrow;
            uint32_t a[4];
            ldsm4t(a, sb + SM_W1 + row * 32 + ((lchk ^ ((row >> 2) & 1)) << 4));
            mma16816(acc, a[0], a[1], a[2], a[3], xb[ks * 2], xb[ks * 2 + 1]);
        }
        __syncwarp();
        if (ft == 0) {
            const uint32_t rb = sb + SM_W1 + u * 1024;
            sts_f1(rb + fg * 4, acc[0]);
            sts_f1(rb + 64 + fg * 4, acc[1]);
            sts_f1(rb + (fg + 8) * 4, acc[2]);
            sts_f1(rb + 64 + (fg + 8) * 4, acc[3]);
        }
        bar_sync(2, NCW * 32);
        if (u == 1 && lane < 16) {
            float2 s = make_float2(0.f, 0.f);
#pragma unroll
            for (int w = 0; w < NCW; w++) {
                float2 v = lds_f2(sb + SM_W1 + w * 1024 + lane * 8);
                s.x += v.x; s.y += v.y;
            }
            float h[2] = {bf16r(bf16r(s.x) + bf_lo(b1pair)), bf16r(bf16r(s.y) + bf_hi(b1pair))};
            float a[2];
#pragma unroll
            for (int i = 0; i < 2; i++) {
                const float e = bf16r(__expf(-fabsf(h[i])));
                const float sp = bf16r(bf16r(log1pf(e)) + fmaxf(h[i], 0.f));
                a[i] = h[i] * bf16r(tanhf(sp));
            }
            const int dp = lane & 7;
            st_ll1(&sc->ax[(((lane >> 3) * 112 + c) * 4 + (dp & 3)) * 2 + (dp >> 2)], pack_bf16(a[0], a[1]), tag);
            TS(11);
        }
    }

    {
        unsigned long long (&w)[3][2] = wo_;
        unsigned long long v[7][2] = {};
        const unsigned long long* psrc = &sc->px[(g16 * 8 + 1) * 64 + lane * 2];
        if (lane < 8) {
            unsigned n = 0;
            while (true) {
                if (!tag_ok(w[0][0], w[0][1], tag)) ld_ll2(so, w[0][0], w[0][1]);
                if (!tag_ok(w[1][0], w[1][1], tag)) ld_ll2(so + 8, w[1][0], w[1][1]);
                if (!tag_ok(w[2][0], w[2][1], tag)) ld_ll2(sa, w[2][0], w[2][1]);
                if ((tag_ok(w[0][0], w[0][1], tag) && tag_ok(w[1][0], w[1][1], tag) && tag_ok(w[2][0], w[2][1], tag)) ||
                    ++n >= SPIN_LIMIT) break;
                __nanosleep(40);
            }
        }
        __syncwarp();
        TS(12);
        float acc[2][4] = {};
        mbar_wait(sb + SM_BAR + (CH_WO + (u >> 2)) * 8);
        TS(13);
#pragma unroll
        for (int ks = 0; ks < 2; ks++) {
            const int row = u * 32 + ks * 16 + lrow;
#pragma unroll
            for (int mt = 0; mt < 2; mt++) {
                uint32_t a[4];
                ldsm4t(a, sb + SM_WO + row * 64 + (((mt * 2 + lchk) ^ ((row >> 1) & 3)) << 4));
                mma16816(acc[mt], a[0], a[1], a[2], a[3], (uint32_t)w[ks][0], (uint32_t)w[ks][1]);
            }
        }
        if (u < 14) {
            mbar_wait(sb + SM_BAR + (CH_W2 + (u >= 7)) * 8);
            TS(14);
            const int row = u * 16 + lrow;
#pragma unroll
            for (int mt = 0; mt < 2; mt++) {
                uint32_t a[4];
                ldsm4t(a, sb + SM_W2 + row * 64 + (((mt * 2 + lchk) ^ ((row >> 1) & 3)) << 4));
                mma16816(acc[mt], a[0], a[1], a[2], a[3], (uint32_t)w[2][0], (uint32_t)w[2][1]);
            }
        }
        __syncwarp();
        if (ft == 0) {
            const uint32_t rb = sb + SM_WO + u * 2048;
#pragma unroll
            for (int mt = 0; mt < 2; mt++) {
                sts_f1(rb + (mt * 16 + fg) * 4, acc[mt][0]);
                sts_f1(rb + 128 + (mt * 16 + fg) * 4, acc[mt][1]);
                sts_f1(rb + (mt * 16 + fg + 8) * 4, acc[mt][2]);
                sts_f1(rb + 128 + (mt * 16 + fg + 8) * 4, acc[mt][3]);
            }
        }
        bar_sync(2, NCW * 32);
        if (u != 0) return;
        float2 s = make_float2(0.f, 0.f);
#pragma unroll
        for (int w2 = 0; w2 < NCW; w2++) {
            float2 v = lds_f2(sb + SM_WO + w2 * 2048 + lane * 8);
            s.x += v.x; s.y += v.y;
        }
        if (r != 0) {
            st_ll2(&sc->px[(g16 * 8 + r) * 64 + lane * 2], __float_as_uint(s.x), __float_as_uint(s.y), tag);
            TS(15);
            return;
        }
        TS(15);
        unsigned n = 0;
        while (true) {
#pragma unroll
            for (int i = 0; i < 7; i++)
                if (!tag_ok(v[i][0], v[i][1], tag)) ld_ll2(psrc + i * 64, v[i][0], v[i][1]);
            bool ok = true;
#pragma unroll
            for (int i = 0; i < 7; i++) ok = ok && tag_ok(v[i][0], v[i][1], tag);
            if (ok || ++n >= SPIN_LIMIT) break;
        }
#pragma unroll
        for (int i = 0; i < 7; i++) { s.x += __uint_as_float((uint32_t)v[i][0]); s.y += __uint_as_float((uint32_t)v[i][1]); }
        reinterpret_cast<uint32_t*>(p.out)[(lane >> 4) * 256 + g16 * 16 + (lane & 15)] =
            pack_bf16(bf_lo(xres) + s.x, bf_hi(xres) + s.y);
        __syncwarp();
        if (c == 0 && lane == 0) sc->epoch = tag;
        TS(16);
    }
}

typedef CUresult (*EncodeTiledFn)(CUtensorMap*, CUtensorMapDataType, cuuint32_t, void*, const cuuint64_t*, const cuuint64_t*,
                                  const cuuint32_t*, const cuuint32_t*, CUtensorMapInterleave, CUtensorMapSwizzle,
                                  CUtensorMapL2promotion, CUtensorMapFloatOOBfill);

void make_map(EncodeTiledFn enc, CUtensorMap* m, const void* base, uint64_t cols, uint64_t rows, uint32_t box_c, uint32_t box_r,
              CUtensorMapSwizzle sw) {
    cuuint64_t gd[2] = {cols, rows};
    cuuint64_t gs[1] = {cols * 2};
    cuuint32_t bd[2] = {box_c, box_r};
    cuuint32_t es[2] = {1, 1};
    enc(m, CU_TENSOR_MAP_DATA_TYPE_BFLOAT16, 2, const_cast<void*>(base), gd, gs, bd, es, CU_TENSOR_MAP_INTERLEAVE_NONE, sw,
        CU_TENSOR_MAP_L2_PROMOTION_L2_128B, CU_TENSOR_MAP_FLOAT_OOB_FILL_NONE);
}

}

extern "C" void kernel_launch(void* const* d_in, const int* in_sizes, int n_in, void* d_out, int out_size) {
    (void)in_sizes; (void)n_in; (void)out_size;
    static EncodeTiledFn enc = nullptr;
    static Scratch* sc = nullptr;
    if (!enc) {
        void* fn = nullptr;
        cudaDriverEntryPointQueryResult st;
        cudaGetDriverEntryPoint("cuTensorMapEncodeTiled", &fn, cudaEnableDefault, &st);
        enc = (EncodeTiledFn)fn;
        cudaFuncSetAttribute(fused_decode_kernel, cudaFuncAttributeMaxDynamicSharedMemorySize, SM_TOTAL);
        void* sp = nullptr;
        cudaGetSymbolAddress(&sp, g_scratch);
        sc = (Scratch*)sp;
    }
    Params p;
    make_map(enc, &p.k, d_in[1], 128, 2 * 8 * SK, 64, 32, CU_TENSOR_MAP_SWIZZLE_128B);
    make_map(enc, &p.v, d_in[2], 128, 2 * 8 * SK, 16, 256, CU_TENSOR_MAP_SWIZZLE_32B);
    make_map(enc, &p.wq, d_in[3], 4096, 512, 32, 128, CU_TENSOR_MAP_SWIZZLE_64B);
    make_map(enc, &p.wo, d_in[4], 512, 4096, 32, 128, CU_TENSOR_MAP_SWIZZLE_64B);
    make_map(enc, &p.w1, d_in[6], FF, 512, 16, 256, CU_TENSOR_MAP_SWIZZLE_32B);
    make_map(enc, &p.w2, d_in[8], 512, FF, 32, 112, CU_TENSOR_MAP_SWIZZLE_64B);
    p.x = (const __nv_bfloat16*)d_in[0];
    p.b1 = (const __nv_bfloat16*)d_in[7];
    p.out = (__nv_bfloat16*)d_out;
    p.sc = sc;
    fused_decode_kernel<<<NCTA, NTHREADS, SM_TOTAL, cudaStreamPerThread>>>(p);
}
```

```cpp
#include <cuda_runtime.h>
#include <cuda_bf16.h>
#include <cuda.h>
#include <stdint.h>

namespace {

constexpr int D_MODEL = 512;
constexpr int SK = 8192;
constexpr int WIN = 2048;
constexpr int WIN0 = SK - WIN;
constexpr int FF = 1792;

constexpr int NCTA = 128;
constexpr int NCW = 8;
constexpr int NCT = NCW * 32;
constexpr int NTHREADS = (NCW + 2) * 32;

constexpr int CH_WQ = 0, CH_K = 4, CH_V = 12, CH_W1 = 20, CH_WO = 22, CH_W2 = 26, NCHUNK = 28;
constexpr int NSLOT = 13;
#define WINDOW 6
__host__ __device__ constexpr int slot_off(int chunk) { return (chunk % NSLOT) * 8192; }

constexpr int BAR_FULL = 0;
constexpr int BAR_EQ = NCHUNK;
constexpr int BAR_EK = BAR_EQ + 1;
constexpr int BAR_EV = BAR_EK + 8;
constexpr int BAR_ST = BAR_EV + 1;
constexpr int BAR_PO = BAR_ST + 1;
constexpr int NBAR = BAR_PO + 1;

constexpr int SM_RING = 0;
constexpr int SM_INB = NSLOT * 8192;
constexpr int SM_INS = SM_INB + 2048;
constexpr int SM_REDA = SM_INS + 256;
constexpr int SM_REDB = SM_REDA + 2048;
constexpr int SM_XN = SM_REDB + 1024;
constexpr int SM_P = SM_XN;
constexpr int SM_Q = SM_XN + 2048;
constexpr int SM_MAX = SM_Q + 1024;
constexpr int SM_SUM = SM_MAX + 128;
constexpr int SM_BAR = SM_SUM + 128;
constexpr int SM_EPOCH = SM_BAR + NBAR * 8;
constexpr int SM_TOTAL = SM_EPOCH + 16;
static_assert(SM_TOTAL <= 115712, "two CTAs must fit on one SM");

constexpr unsigned SPIN_LIMIT = 1u << 22;

struct Scratch {
    unsigned epoch;
    unsigned pad[31];
    unsigned long long qx[2 * 32 * 64];
    unsigned long long ox[2 * 256 * 8];
    unsigned long long ax[2 * 112 * 8];
    unsigned long long px[16 * 8 * 64];
};

__device__ Scratch g_scratch;

struct Params {
    CUtensorMap wq, k, v, w1, wo, w2;
    const __nv_bfloat16* x;
    const __nv_bfloat16* b1;
    __nv_bfloat16* out;
    Scratch* sc;
};

__device__ __forceinline__ uint32_t smem_u32(const void* p) { return (uint32_t)__cvta_generic_to_shared(p); }
__device__ __forceinline__ void mbar_init(uint32_t bar, uint32_t cnt) {
    asm volatile("mbarrier.init.shared::cta.b64 [%0], %1;" ::"r"(bar), "r"(cnt) : "memory");
}
__device__ __forceinline__ void mbar_expect_tx(uint32_t bar, uint32_t bytes) {
    asm volatile("mbarrier.arrive.expect_tx.shared::cta.b64 _, [%0], %1;" ::"r"(bar), "r"(bytes) : "memory");
}
__device__ __forceinline__ void mbar_arrive(uint32_t bar) {
    asm volatile("mbarrier.arrive.shared::cta.b64 _, [%0];" ::"r"(bar) : "memory");
}
__device__ __forceinline__ void mbar_wait(uint32_t bar) {
    unsigned n = 0;
    uint32_t ok;
    do {
        asm volatile("{\n.reg .pred p;\nmbarrier.try_wait.parity.shared::cta.b64 p, [%1], 0;\nselp.u32 %0, 1, 0, p;\n}"
                     : "=r"(ok) : "r"(bar) : "memory");
    } while (!ok && ++n < SPIN_LIMIT);
}
__device__ __forceinline__ void mbar_wait_cluster(uint32_t bar) {
    unsigned n = 0;
    uint32_t ok;
    do {
        asm volatile("{\n.reg .pred p;\nmbarrier.try_wait.parity.acquire.cluster.shared::cta.b64 p, [%1], 0;\nselp.u32 %0, 1, 0, p;\n}"
                     : "=r"(ok) : "r"(bar) : "memory");
    } while (!ok && ++n < SPIN_LIMIT);
}
__device__ __forceinline__ void tma2d(uint32_t dst, const CUtensorMap* tm, int c0, int c1, uint32_t bar) {
    asm volatile("cp.async.bulk.tensor.2d.shared::cluster.global.mbarrier::complete_tx::bytes [%0], [%1, {%3, %4}], [%2];"
                 ::"r"(dst), "l"((uint64_t)tm), "r"(bar), "r"(c0), "r"(c1) : "memory");
}
__device__ __forceinline__ uint32_t mapa(uint32_t addr, uint32_t rank) {
    uint32_t r;
    asm("mapa.shared::cluster.u32 %0, %1, %2;" : "=r"(r) : "r"(addr), "r"(rank));
    return r;
}
__device__ __forceinline__ void bar_sync(int id, int n) { asm volatile("bar.sync %0, %1;" ::"r"(id), "r"(n) : "memory"); }
__device__ __forceinline__ void bar_arrive(int id, int n) { asm volatile("bar.arrive %0, %1;" ::"r"(id), "r"(n) : "memory"); }

__device__ __forceinline__ void ldsm4(uint32_t (&r)[4], uint32_t addr) {
    asm volatile("ldmatrix.sync.aligned.m8n8.x4.shared.b16 {%0,%1,%2,%3}, [%4];"
                 : "=r"(r[0]), "=r"(r[1]), "=r"(r[2]), "=r"(r[3]) : "r"(addr) : "memory");
}
__device__ __forceinline__ void ldsm4t(uint32_t (&r)[4], uint32_t addr) {
    asm volatile("ldmatrix.sync.aligned.m8n8.x4.trans.shared.b16 {%0,%1,%2,%3}, [%4];"
                 : "=r"(r[0]), "=r"(r[1]), "=r"(r[2]), "=r"(r[3]) : "r"(addr) : "memory");
}
__device__ __forceinline__ void mma16816(float (&c)[4], uint32_t a0, uint32_t a1, uint32_t a2, uint32_t a3, uint32_t b0, uint32_t b1) {
    asm volatile("mma.sync.aligned.m16n8k16.row.col.f32.bf16.bf16.f32 {%0,%1,%2,%3}, {%4,%5,%6,%7}, {%8,%9}, {%0,%1,%2,%3};"
                 : "+f"(c[0]), "+f"(c[1]), "+f"(c[2]), "+f"(c[3])
                 : "r"(a0), "r"(a1), "r"(a2), "r"(a3), "r"(b0), "r"(b1));
}
__device__ __forceinline__ void st_ll1(unsigned long long* p, uint32_t d, uint32_t tag) {
    unsigned long long w = ((unsigned long long)tag << 32) | d;
    asm volatile("st.relaxed.gpu.global.b64 [%0], %1;" ::"l"(p), "l"(w) : "memory");
}
__device__ __forceinline__ void st_ll2(unsigned long long* p, uint32_t d0, uint32_t d1, uint32_t tag) {
    unsigned long long w0 = ((unsigned long long)tag << 32) | d0, w1 = ((unsigned long long)tag << 32) | d1;
    asm volatile("st.relaxed.gpu.global.v2.b64 [%0], {%1, %2};" ::"l"(p), "l"(w0), "l"(w1) : "memory");
}
__device__ __forceinline__ void ld_ll2(const unsigned long long* p, unsigned long long& w0, unsigned long long& w1) {
    asm volatile("ld.relaxed.gpu.global.v2.b64 {%0, %1}, [%2];" : "=l"(w0), "=l"(w1) : "l"(p) : "memory");
}
__device__ __forceinline__ bool tag_ok(unsigned long long w0, unsigned long long w1, uint32_t tag) {
    return (uint32_t)(w0 >> 32) == tag && (uint32_t)(w1 >> 32) == tag;
}
__device__ __forceinline__ float ex2(float x) {
    float y;
    asm("ex2.approx.ftz.f32 %0, %1;" : "=f"(y) : "f"(x));
    return y;
}
__device__ __forceinline__ float bf16r(float x) { return __bfloat162float(__float2bfloat16_rn(x)); }
__device__ __forceinline__ uint32_t pack_bf16(float lo, float hi) {
    __nv_bfloat162 v = __floats2bfloat162_rn(lo, hi);
    return *reinterpret_cast<uint32_t*>(&v);
}
__device__ __forceinline__ float bf_lo(uint32_t u) { return __uint_as_float(u << 16); }
__device__ __forceinline__ float bf_hi(uint32_t u) { return __uint_as_float(u & 0xffff0000u); }
__device__ __forceinline__ float2 lds_f2(uint32_t a) {
    float2 v;
    asm volatile("ld.shared.v2.f32 {%0, %1}, [%2];" : "=f"(v.x), "=f"(v.y) : "r"(a) : "memory");
    return v;
}
__device__ __forceinline__ float lds_f1(uint32_t a) {
    float v;
    asm volatile("ld.shared.f32 %0, [%1];" : "=f"(v) : "r"(a) : "memory");
    return v;
}
__device__ __forceinline__ uint32_t lds_u1(uint32_t a) {
    uint32_t v;
    asm volatile("ld.shared.u32 %0, [%1];" : "=r"(v) : "r"(a) : "memory");
    return v;
}
__device__ __forceinline__ void lds_u4(uint32_t* r, uint32_t a) {
    asm volatile("ld.shared.v4.u32 {%0,%1,%2,%3}, [%4];" : "=r"(r[0]), "=r"(r[1]), "=r"(r[2]), "=r"(r[3]) : "r"(a) : "memory");
}
__device__ __forceinline__ void sts_f1(uint32_t a, float v) { asm volatile("st.shared.f32 [%0], %1;" ::"r"(a), "f"(v) : "memory"); }
__device__ __forceinline__ void sts_u1(uint32_t a, uint32_t v) { asm volatile("st.shared.u32 [%0], %1;" ::"r"(a), "r"(v) : "memory"); }
__device__ __forceinline__ void sts_u4(uint32_t a, uint32_t x, uint32_t y, uint32_t z, uint32_t w) {
    asm volatile("st.shared.v4.u32 [%0], {%1,%2,%3,%4};" ::"r"(a), "r"(x), "r"(y), "r"(z), "r"(w) : "memory");
}

#define TS(i) do { } while (0)

__device__ __forceinline__ void gemv_tile64(float (&acc)[2][4], uint32_t base, int row, int lchk, uint32_t b0, uint32_t b1) {
    uint32_t a0[4], a1[4];
    const uint32_t ra = base + row * 64;
    const int sw = (row >> 1) & 3;
    ldsm4t(a0, ra + ((lchk ^ sw) << 4));
    ldsm4t(a1, ra + (((2 + lchk) ^ sw) << 4));
    mma16816(acc[0], a0[0], a0[1], a0[2], a0[3], b0, b1);
    mma16816(acc[1], a1[0], a1[1], a1[2], a1[3], b0, b1);
}

__global__ void __cluster_dims__(8, 1, 1) __launch_bounds__(NTHREADS, 2) fused_decode_kernel(const __grid_constant__ Params p) {
    extern __shared__ __align__(1024) uint8_t smem[];
    const uint32_t sb = smem_u32(smem);
    const uint32_t bars = sb + SM_BAR;
    const int c = blockIdx.x;
    const int warp = threadIdx.x >> 5, lane = threadIdx.x & 31;
    const int bh = c >> 3, j = c & 7;
    const int r = c >> 4, g16 = c & 15;

    if (warp == NCW) {
        if (lane == 0) {
#pragma unroll
            for (int i = 0; i < 4; i++) mbar_init(bars + i * 8, 1);
            asm volatile("fence.proxy.async.shared::cta;" ::: "memory");
#pragma unroll
            for (int i = 0; i < CH_K; i++) {
                mbar_expect_tx(bars + i * 8, 8192);
                tma2d(sb + slot_off(i), &p.wq, 32 * c, 128 * i, bars + i * 8);
                TS(i);
            }
#pragma unroll
            for (int k = 4; k < NCHUNK; k++) mbar_init(bars + k * 8, 1);
            mbar_init(bars + BAR_EQ * 8, NCW);
#pragma unroll
            for (int k = 0; k < 8; k++) mbar_init(bars + (BAR_EK + k) * 8, 1);
            mbar_init(bars + BAR_EV * 8, NCW);
            asm volatile("fence.proxy.async.shared::cta;" ::: "memory");
        }
        __syncwarp();
        bar_arrive(1, NTHREADS);
        asm volatile("barrier.cluster.arrive.relaxed.aligned;" ::: "memory");
        if (lane == 0) {
            const int krow = bh * SK + WIN0 + j * 256;
#pragma unroll
            for (int i = CH_K; i < NCHUNK; i++) {
                const uint32_t bar = bars + i * 8;
                const uint32_t dst = sb + slot_off(i);
                if (i >= WINDOW) mbar_wait(bar - WINDOW * 8);
                if (i == NSLOT) mbar_wait(bars + BAR_EQ * 8);
                if (i >= NSLOT + CH_K && i < NSLOT + CH_V) mbar_wait(bars + (BAR_EK + i - NSLOT - CH_K) * 8);
                if (i == NSLOT + CH_V) mbar_wait(bars + BAR_EV * 8);
                if (i < CH_V) {
                    const int q = i - CH_K;
                    mbar_expect_tx(bar, 8192);
                    tma2d(dst, &p.k, 0, krow + q * 32, bar);
                    tma2d(dst + 4096, &p.k, 64, krow + q * 32, bar);
                } else if (i < CH_W1) {
                    const int q = i - CH_V;
                    mbar_expect_tx(bar, 8192);
                    tma2d(dst, &p.v, 0, krow + q * 32, bar);
                    tma2d(dst + 4096, &p.v, 64, krow + q * 32, bar);
                } else if (i < CH_WO) {
                    const int q = i - CH_W1;
                    if (c < 112) {
                        mbar_expect_tx(bar, 8192);
                        tma2d(dst, &p.w1, 16 * c, 256 * q, bar);
                    } else {
                        mbar_expect_tx(bar, 0);
                    }
                } else if (i < CH_W2) {
                    const int q = i - CH_WO;
                    mbar_expect_tx(bar, 8192);
                    tma2d(dst, &p.wo, 32 * g16, 512 * r + 128 * q, bar);
                } else {
                    const int q = i - CH_W2;
                    mbar_expect_tx(bar, 7168);
                    tma2d(dst, &p.w2, 32 * g16, 224 * r + 112 * q, bar);
                }
                TS(i);
            }
        }
        return;
    }

    Scratch* const sc = p.sc;
    const float LOG2E = 1.4426950408889634f;

    if (warp == NCW + 1) {
        const uint32_t tag = *reinterpret_cast<volatile unsigned*>(&sc->epoch) + 1u;
        if (lane == 0) {
            mbar_init(bars + BAR_ST * 8, 1);
            mbar_init(bars + BAR_PO * 8, 1);
            asm volatile("fence.mbarrier_init.release.cluster;" ::: "memory");
            mbar_expect_tx(bars + BAR_ST * 8, 256);
            mbar_expect_tx(bars + BAR_PO * 8, 2048);
            sts_u1(sb + SM_EPOCH, tag);
        }
        __syncwarp();
        bar_arrive(1, NTHREADS);
        asm volatile("barrier.cluster.arrive.release.aligned;" ::: "memory");
        TS(0);
        {
            const unsigned long long* src = &sc->qx[((bh >> 3) * 32 + (bh & 7) * 4) * 64 + 2 * lane];
            unsigned pend = 0xf, n = 0;
            while (true) {
                unsigned long long w[4][2];
#pragma unroll
                for (int h = 0; h < 4; h++)
                    if (pend >> h & 1) ld_ll2(src + h * 64, w[h][0], w[h][1]);
#pragma unroll
                for (int h = 0; h < 4; h++)
                    if ((pend >> h & 1) && tag_ok(w[h][0], w[h][1], tag)) {
                        const uint32_t dst = sb + SM_Q + ((h * 4 + ((2 * lane) & 3)) * 16 + (lane >> 1)) * 4;
                        sts_u1(dst, (uint32_t)w[h][0]);
                        sts_u1(dst + 64, (uint32_t)w[h][1]);
                        pend &= ~(1u << h);
                    }
                if (__all_sync(~0u, pend == 0) || ++n >= SPIN_LIMIT) break;
                __nanosleep(100);
            }
        }
        bar_arrive(3, NCT + 32);
        TS(1);
        asm volatile("barrier.cluster.wait.acquire.aligned;" ::: "memory");
        bar_sync(4, NCT + 32);
        {
            float mx = lds_f1(sb + SM_MAX + lane * 4);
            float sm = lds_f1(sb + SM_SUM + lane * 4);
#pragma unroll
            for (int o = 4; o < 32; o <<= 1) { mx = fmaxf(mx, __shfl_xor_sync(~0u, mx, o)); sm += __shfl_xor_sync(~0u, sm, o); }
            const uint32_t dst = mapa(sb + SM_INS + (j * 4 + (lane & 3)) * 8, lane >> 2);
            const uint32_t rbar = mapa(bars + BAR_ST * 8, lane >> 2);
            asm volatile("st.async.weak.shared::cluster.mbarrier::complete_tx::bytes.v2.f32 [%0], {%1, %2}, [%3];"
                         ::"r"(dst), "f"(mx), "f"(sm), "r"(rbar) : "memory");
        }
        TS(2);
        float coef[8];
        {
            mbar_wait_cluster(bars + BAR_ST * 8);
            const float2 st = lds_f2(sb + SM_INS + lane * 8);
            float gm = st.x;
#pragma unroll
            for (int o = 4; o < 32; o <<= 1) gm = fmaxf(gm, __shfl_xor_sync(~0u, gm, o));
            const float wj = ex2((st.x - gm) * LOG2E);
            float gl = wj * st.y;
#pragma unroll
            for (int o = 4; o < 32; o <<= 1) gl += __shfl_xor_sync(~0u, gl, o);
            const float cj = wj / gl;
#pragma unroll
            for (int k = 0; k < 8; k++) coef[k] = __shfl_sync(~0u, cj, k * 4 + (lane >> 3));
        }
        TS(3);
        mbar_wait_cluster(bars + BAR_PO * 8);
        {
            float o0 = 0.f, o1 = 0.f;
#pragma unroll
            for (int k = 0; k < 8; k++) {
                const float2 v = lds_f2(sb + SM_INB + k * 256 + lane * 8);
                o0 = fmaf(coef[k], v.x, o0);
                o1 = fmaf(coef[k], v.y, o1);
            }
            const int head = (bh & 7) * 4 + (lane >> 3);
            st_ll1(&sc->ox[((bh >> 3) * 256 + head * 8 + j) * 8 + (lane & 7)], pack_bf16(o0, o1), tag);
        }
        TS(4);
        return;
    }

    const int u = warp;
    const int fg = lane >> 2, ft = lane & 3;
    asm volatile("barrier.cluster.arrive.relaxed.aligned;" ::: "memory");

    uint32_t xres = 0;
    uint32_t b1pair = 0;
    if (u < 2) {
        const uint4* x4 = reinterpret_cast<const uint4*>(p.x) + u * 64 + lane * 2;
        const uint4 v0 = __ldg(x4), v1 = __ldg(x4 + 1);
        if (u == 0) xres = __ldg(reinterpret_cast<const uint32_t*>(p.x) + (lane >> 4) * 256 + g16 * 16 + (lane & 15));
        if (u == 1 && c < 112) b1pair = __ldg(reinterpret_cast<const uint32_t*>(p.b1) + c * 8 + (lane & 7));
        const uint32_t a[8] = {v0.x, v0.y, v0.z, v0.w, v1.x, v1.y, v1.z, v1.w};
        float s0 = 0.f;
#pragma unroll
        for (int i = 0; i < 8; i++) s0 += bf_lo(a[i]) + bf_hi(a[i]);
#pragma unroll
        for (int o = 16; o > 0; o >>= 1) s0 += __shfl_xor_sync(~0u, s0, o);
        const float m0 = s0 * (1.f / D_MODEL);
        float q0 = 0.f;
#pragma unroll
        for (int i = 0; i < 8; i++) {
            float d;
            d = bf_lo(a[i]) - m0; q0 += d * d; d = bf_hi(a[i]) - m0; q0 += d * d;
        }
#pragma unroll
        for (int o = 16; o > 0; o >>= 1) q0 += __shfl_xor_sync(~0u, q0, o);
        const float mean = bf16r(m0);
        const float var = bf16r(q0 * (1.f / D_MODEL));
        const float den = bf16r(sqrtf(bf16r(var + 1e-5f)));
        uint32_t o[8];
#pragma unroll
        for (int i = 0; i < 8; i++) o[i] = pack_bf16(bf16r(bf_lo(a[i]) - mean) / den, bf16r(bf_hi(a[i]) - mean) / den);
        const uint32_t dst = sb + SM_XN + u * 1024 + lane * 32;
        sts_u4(dst, o[0], o[1], o[2], o[3]);
        sts_u4(dst + 16, o[4], o[5], o[6], o[7]);
        TS(0);
    }

    const int lrow = (lane & 7) + ((lane >> 4) << 3);
    const int lchk = (lane >> 3) & 1;

    bar_sync(1, NTHREADS);
    const uint32_t tag = lds_u1(sb + SM_EPOCH);
    uint32_t xb[4][2];
#pragma unroll
    for (int q = 0; q < 4; q++) {
        xb[q][0] = lds_u1(sb + SM_XN + (fg & 1) * 1024 + (q * 64 + u * 8 + ft) * 4);
        xb[q][1] = lds_u1(sb + SM_XN + (fg & 1) * 1024 + (q * 64 + u * 8 + 4 + ft) * 4);
    }

    {
        float acc[2][4] = {};
#pragma unroll
        for (int q = 0; q < 4; q++) {
            mbar_wait(bars + (CH_WQ + q) * 8);
            gemv_tile64(acc, sb + slot_off(CH_WQ + q), u * 16 + lrow, lchk, xb[q][0], xb[q][1]);
        }
        TS(1);
        if (lane == 0) mbar_arrive(bars + BAR_EQ * 8);
        if (ft == 0) {
            const uint32_t rb = sb + SM_REDA + u * 256;
#pragma unroll
            for (int mt = 0; mt < 2; mt++) {
                sts_f1(rb + (mt * 16 + fg) * 4, acc[mt][0]);
                sts_f1(rb + 128 + (mt * 16 + fg) * 4, acc[mt][1]);
                sts_f1(rb + (mt * 16 + fg + 8) * 4, acc[mt][2]);
                sts_f1(rb + 128 + (mt * 16 + fg + 8) * 4, acc[mt][3]);
            }
        }
    }
    bar_sync(2, NCT);
    if (u == 0) {
        float2 s = make_float2(0.f, 0.f);
#pragma unroll
        for (int w = 0; w < NCW; w++) {
            float2 v = lds_f2(sb + SM_REDA + w * 256 + lane * 8);
            s.x += v.x; s.y += v.y;
        }
        st_ll1(&sc->qx[((lane >> 4) * 32 + (c >> 2)) * 64 + (c & 3) * 16 + (lane & 15)], pack_bf16(s.x, s.y), tag);
        TS(2);
    }
    asm volatile("barrier.cluster.wait.acquire.aligned;" ::: "memory");
    bar_sync(3, NCT + 32);
    TS(3);

    {
        uint32_t qa[16];
#pragma unroll
        for (int i = 0; i < 4; i++) lds_u4(qa + 4 * i, sb + SM_Q + ((fg & 3) * 4 + ft) * 64 + i * 16);
        mbar_wait(bars + (CH_K + u) * 8);
        TS(4);
        float acc[4][4] = {};
        const uint32_t kb = sb + ((CH_K + u) % NSLOT) * 8192 + (lane & 7) * 128;
#pragma unroll
        for (int q = 0; q < 4; q++) {
            const int chunk = q * 4 + (lane >> 3);
            const uint32_t off = (chunk >> 3) * 4096 + (((chunk & 7) ^ (lane & 7)) << 4);
#pragma unroll
            for (int nt = 0; nt < 4; nt++) {
                uint32_t b[4];
                ldsm4(b, kb + nt * 1024 + off);
                mma16816(acc[nt], qa[4 * q], 0u, qa[4 * q + 1], 0u, b[0], b[1]);
                mma16816(acc[nt], qa[4 * q + 2], 0u, qa[4 * q + 3], 0u, b[2], b[3]);
            }
        }
        if (lane == 0) mbar_arrive(bars + (BAR_EK + u) * 8);
        const float scale = 0.08838834764831845f;
        float sv[8];
#pragma unroll
        for (int i = 0; i < 8; i++) sv[i] = bf16r(bf16r(acc[i >> 1][i & 1]) * scale);
        float m = fmaxf(fmaxf(fmaxf(sv[0], sv[1]), fmaxf(sv[2], sv[3])), fmaxf(fmaxf(sv[4], sv[5]), fmaxf(sv[6], sv[7])));
        m = fmaxf(m, __shfl_xor_sync(~0u, m, 1));
        m = fmaxf(m, __shfl_xor_sync(~0u, m, 2));
        if (lane < 16 && ft == 0) sts_f1(sb + SM_MAX + (u * 4 + fg) * 4, m);
        TS(5);
        bar_sync(2, NCT);
        m = lds_f1(sb + SM_MAX + ((ft + 4 * (fg >> 2)) * 4 + (fg & 3)) * 4);
        m = fmaxf(m, __shfl_xor_sync(~0u, m, 1));
        m = fmaxf(m, __shfl_xor_sync(~0u, m, 2));
        m = fmaxf(m, __shfl_xor_sync(~0u, m, 16));
#pragma unroll
        for (int i = 0; i < 8; i++) sv[i] = ex2((sv[i] - m) * LOG2E);
        float l = ((sv[0] + sv[1]) + (sv[2] + sv[3])) + ((sv[4] + sv[5]) + (sv[6] + sv[7]));
        l += __shfl_xor_sync(~0u, l, 1);
        l += __shfl_xor_sync(~0u, l, 2);
        if (lane < 16) {
            sts_u4(sb + SM_P + (u * 16 + lane) * 16, pack_bf16(sv[0], sv[1]), pack_bf16(sv[2], sv[3]), pack_bf16(sv[4], sv[5]),
                   pack_bf16(sv[6], sv[7]));
            if (ft == 0) sts_f1(sb + SM_SUM + (u * 4 + fg) * 4, l);
        }
        bar_sync(4, NCT + 32);
        TS(6);
    }

    unsigned long long w[6][2] = {};
    const unsigned long long* so = &sc->ox[(((fg & 1) * 256 + r * 32 + u) * 4 + ft) * 2];
    const unsigned long long* sa = &sc->ax[(((fg & 1) * 112 + r * 14 + (u < 7 ? u : 0)) * 4 + ft) * 2];
    {
        float acc[2][4] = {};
        const uint32_t voff = (u >> 2) * 4096 + lane * 128;
        const uint32_t c0 = (((u & 3) * 2) ^ (lane & 7)) << 4, c1 = (((u & 3) * 2 + 1) ^ (lane & 7)) << 4;
#pragma unroll
        for (int i = 0; i < 8; i++) {
            uint32_t pa[4], b0[4], b1[4];
            lds_u4(pa, sb + SM_P + (i * 16 + (lane & 15)) * 16);
            mbar_wait(bars + (CH_V + i) * 8);
            ldsm4t(b0, sb + slot_off(CH_V + i) + voff + c0);
            ldsm4t(b1, sb + slot_off(CH_V + i) + voff + c1);
            mma16816(acc[0], pa[0], 0u, pa[1], 0u, b0[0], b0[1]);
            mma16816(acc[1], pa[0], 0u, pa[1], 0u, b1[0], b1[1]);
            mma16816(acc[0], pa[2], 0u, pa[3], 0u, b0[2], b0[3]);
            mma16816(acc[1], pa[2], 0u, pa[3], 0u, b1[2], b1[3]);
            if (i == 2 && lane == 0) mbar_arrive(bars + BAR_EV * 8);
        }
        TS(8);
        if (lane < 16) {
            const uint32_t dst = mapa(sb + SM_INB + j * 256 + lane * 16, u);
            const uint32_t rbar = mapa(bars + BAR_PO * 8, u);
            asm volatile("st.async.weak.shared::cluster.mbarrier::complete_tx::bytes.v4.f32 [%0], {%1, %2, %3, %4}, [%5];"
                         ::"r"(dst), "f"(acc[0][0]), "f"(acc[0][1]), "f"(acc[1][0]), "f"(acc[1][1]), "r"(rbar) : "memory");
        }
        TS(9);
    }

    if (c < 112) {
        float acc[4] = {};
#pragma unroll
        for (int q = 0; q < 4; q++) {
            if ((q & 1) == 0) mbar_wait(bars + (CH_W1 + (q >> 1)) * 8);
            const int row = (q & 1) * 128 + u * 16 + lrow;
            uint32_t a[4];
            ldsm4t(a, sb + slot_off(CH_W1 + (q >> 1)) + row * 32 + ((lchk ^ ((row >> 2) & 1)) << 4));
            mma16816(acc, a[0], a[1], a[2], a[3], xb[q][0], xb[q][1]);
        }
        TS(10);
        if (ft == 0) {
            const uint32_t rb = sb + SM_REDB + u * 128;
            sts_f1(rb + fg * 4, acc[0]);
            sts_f1(rb + 64 + fg * 4, acc[1]);
            sts_f1(rb + (fg + 8) * 4, acc[2]);
            sts_f1(rb + 64 + (fg + 8) * 4, acc[3]);
        }
        bar_sync(2, NCT);
        if (u == 1 && lane < 16) {
            float2 s = make_float2(0.f, 0.f);
#pragma unroll
            for (int k = 0; k < NCW; k++) {
                float2 v = lds_f2(sb + SM_REDB + k * 128 + lane * 8);
                s.x += v.x; s.y += v.y;
            }
            float h[2] = {bf16r(bf16r(s.x) + bf_lo(b1pair)), bf16r(bf16r(s.y) + bf_hi(b1pair))};
            float a[2];
#pragma unroll
            for (int i = 0; i < 2; i++) {
                const float e = bf16r(__expf(-fabsf(h[i])));
                const float sp = bf16r(bf16r(log1pf(e)) + fmaxf(h[i], 0.f));
                a[i] = h[i] * bf16r(tanhf(sp));
            }
            const int dp = lane & 7;
            st_ll1(&sc->ax[(((lane >> 3) * 112 + c) * 4 + (dp & 3)) * 2 + (dp >> 2)], pack_bf16(a[0], a[1]), tag);
            TS(11);
        }
    }

    {
        unsigned long long v[7][2] = {};
        const unsigned long long* psrc = &sc->px[(g16 * 8 + 1) * 64 + lane * 2];
        if (u == 0 && r == 0) {
#pragma unroll
            for (int i = 0; i < 7; i++) ld_ll2(psrc + i * 64, v[i][0], v[i][1]);
        }
        if (lane < 8) {
            unsigned n = 0;
            while (true) {
#pragma unroll
                for (int q = 0; q < 4; q++)
                    if (!tag_ok(w[q][0], w[q][1], tag)) ld_ll2(so + q * 64, w[q][0], w[q][1]);
#pragma unroll
                for (int q = 0; q < 2; q++)
                    if (!tag_ok(w[4 + q][0], w[4 + q][1], tag)) ld_ll2(sa + q * 56, w[4 + q][0], w[4 + q][1]);
                bool ok = true;
#pragma unroll
                for (int q = 0; q < 6; q++) ok = ok && tag_ok(w[q][0], w[q][1], tag);
                if (ok || ++n >= SPIN_LIMIT) break;
                __nanosleep(40);
            }
        }
        __syncwarp();
        TS(12);
        float acc[2][4] = {};
#pragma unroll
        for (int q = 0; q < 4; q++) {
            mbar_wait(bars + (CH_WO + q) * 8);
            gemv_tile64(acc, sb + slot_off(CH_WO + q), u * 16 + lrow, lchk, (uint32_t)w[q][0], (uint32_t)w[q][1]);
        }
        TS(13);
        if (u < 7) {
#pragma unroll
            for (int q = 0; q < 2; q++) {
                mbar_wait(bars + (CH_W2 + q) * 8);
                gemv_tile64(acc, sb + slot_off(CH_W2 + q), u * 16 + lrow, lchk, (uint32_t)w[4 + q][0], (uint32_t)w[4 + q][1]);
            }
        }
        TS(14);
        if (ft == 0) {
            const uint32_t rb = sb + SM_REDA + u * 256;
#pragma unroll
            for (int mt = 0; mt < 2; mt++) {
                sts_f1(rb + (mt * 16 + fg) * 4, acc[mt][0]);
                sts_f1(rb + 128 + (mt * 16 + fg) * 4, acc[mt][1]);
                sts_f1(rb + (mt * 16 + fg + 8) * 4, acc[mt][2]);
                sts_f1(rb + 128 + (mt * 16 + fg + 8) * 4, acc[mt][3]);
            }
        }
        if (u != 0) { bar_arrive(2, NCT); return; }
        bar_sync(2, NCT);
        float2 s = make_float2(0.f, 0.f);
#pragma unroll
        for (int k = 0; k < NCW; k++) {
            float2 t = lds_f2(sb + SM_REDA + k * 256 + lane * 8);
            s.x += t.x; s.y += t.y;
        }
        if (r != 0) {
            st_ll2(&sc->px[(g16 * 8 + r) * 64 + lane * 2], __float_as_uint(s.x), __float_as_uint(s.y), tag);
            TS(15);
            return;
        }
        TS(15);
        unsigned n = 0;
        while (true) {
#pragma unroll
            for (int i = 0; i < 7; i++)
                if (!tag_ok(v[i][0], v[i][1], tag)) ld_ll2(psrc + i * 64, v[i][0], v[i][1]);
            bool ok = true;
#pragma unroll
            for (int i = 0; i < 7; i++) ok = ok && tag_ok(v[i][0], v[i][1], tag);
            if (ok || ++n >= SPIN_LIMIT) break;
        }
#pragma unroll
        for (int i = 0; i < 7; i++) { s.x += __uint_as_float((uint32_t)v[i][0]); s.y += __uint_as_float((uint32_t)v[i][1]); }
        reinterpret_cast<uint32_t*>(p.out)[(lane >> 4) * 256 + g16 * 16 + (lane & 15)] =
            pack_bf16(bf_lo(xres) + s.x, bf_hi(xres) + s.y);
        __syncwarp();
        if (c == 0 && lane == 0) sc->epoch = tag;
        TS(16);
    }
}

typedef CUresult (*EncodeTiledFn)(CUtensorMap*, CUtensorMapDataType, cuuint32_t, void*, const cuuint64_t*, const cuuint64_t*,
                                  const cuuint32_t*, const cuuint32_t*, CUtensorMapInterleave, CUtensorMapSwizzle,
                                  CUtensorMapL2promotion, CUtensorMapFloatOOBfill);

void make_map(EncodeTiledFn enc, CUtensorMap* m, const void* base, uint64_t cols, uint64_t rows, uint32_t box_c, uint32_t box_r,
              CUtensorMapSwizzle sw) {
    cuuint64_t gd[2] = {cols, rows};
    cuuint64_t gs[1] = {cols * 2};
    cuuint32_t bd[2] = {box_c, box_r};
    cuuint32_t es[2] = {1, 1};
    enc(m, CU_TENSOR_MAP_DATA_TYPE_BFLOAT16, 2, const_cast<void*>(base), gd, gs, bd, es, CU_TENSOR_MAP_INTERLEAVE_NONE, sw,
        CU_TENSOR_MAP_L2_PROMOTION_L2_128B, CU_TENSOR_MAP_FLOAT_OOB_FILL_NONE);
}

}

extern "C" void kernel_launch(void* const* d_in, const int* in_sizes, int n_in, void* d_out, int out_size) {
    (void)in_sizes; (void)n_in; (void)out_size;
    static EncodeTiledFn enc = nullptr;
    static Scratch* sc = nullptr;
    if (!enc) {
        void* fn = nullptr;
        cudaDriverEntryPointQueryResult st;
        cudaGetDriverEntryPoint("cuTensorMapEncodeTiled", &fn, cudaEnableDefault, &st);
        enc = (EncodeTiledFn)fn;
        cudaFuncSetAttribute(fused_decode_kernel, cudaFuncAttributeMaxDynamicSharedMemorySize, SM_TOTAL);
        void* sp = nullptr;
        cudaGetSymbolAddress(&sp, g_scratch);
        sc = (Scratch*)sp;
    }
    Params p;
    make_map(enc, &p.k, d_in[1], 128, 2 * 8 * SK, 64, 32, CU_TENSOR_MAP_SWIZZLE_128B);
    make_map(enc, &p.v, d_in[2], 128, 2 * 8 * SK, 64, 32, CU_TENSOR_MAP_SWIZZLE_128B);
    make_map(enc, &p.wq, d_in[3], 4096, 512, 32, 128, CU_TENSOR_MAP_SWIZZLE_64B);
    make_map(enc, &p.wo, d_in[4], 512, 4096, 32, 128, CU_TENSOR_MAP_SWIZZLE_64B);
    make_map(enc, &p.w1, d_in[6], FF, 512, 16, 256, CU_TENSOR_MAP_SWIZZLE_32B);
    make_map(enc, &p.w2, d_in[8], 512, FF, 32, 112, CU_TENSOR_MAP_SWIZZLE_64B);
    p.x = (const __nv_bfloat16*)d_in[0];
    p.b1 = (const __nv_bfloat16*)d_in[7];
    p.out = (__nv_bfloat16*)d_out;
    p.sc = sc;
    fused_decode_kernel<<<NCTA, NTHREADS, SM_TOTAL, cudaStreamPerThread>>>(p);
}
```

```cpp
#include <cuda_runtime.h>
#include <cuda_bf16.h>
#include <cuda.h>
#include <stdint.h>

namespace {

constexpr int D_MODEL = 512;
constexpr int SK = 8192;
constexpr int WIN = 2048;
constexpr int WIN0 = SK - WIN;
constexpr int FF = 1792;

constexpr int NCTA = 128;
constexpr int NCW = 8;
constexpr int NCT = NCW * 32;
constexpr int NTHREADS = (NCW + 2) * 32;

constexpr int CH_WQ = 0, CH_W1 = 4, CH_K = 6, CH_V = 14, CH_WO = 22, CH_W2 = 26, NCHUNK = 28;
constexpr int NSLOT = 13;
#define WINDOW 6
__host__ __device__ constexpr int slot_off(int chunk) { return (chunk % NSLOT) * 8192; }

constexpr int BAR_FULL = 0;
constexpr int BAR_EQ = NCHUNK;
constexpr int BAR_EK = BAR_EQ + 1;
constexpr int BAR_EV = BAR_EK + 8;
constexpr int BAR_ST = BAR_EV + 1;
constexpr int BAR_PO = BAR_ST + 1;
constexpr int NBAR = BAR_PO + 1;

constexpr int SM_RING = 0;
constexpr int SM_INB = NSLOT * 8192;
constexpr int SM_INS = SM_INB + 2048;
constexpr int SM_REDA = SM_INS + 256;
constexpr int SM_REDB = SM_REDA + 2048;
constexpr int SM_XN = SM_REDB + 1024;
constexpr int SM_P = SM_XN;
constexpr int SM_Q = SM_XN + 2048;
constexpr int SM_MAX = SM_Q + 1024;
constexpr int SM_SUM = SM_MAX + 128;
constexpr int SM_BAR = SM_SUM + 128;
constexpr int SM_EPOCH = SM_BAR + NBAR * 8;
constexpr int SM_TOTAL = SM_EPOCH + 16;
static_assert(SM_TOTAL <= 115712, "two CTAs must fit on one SM");

constexpr unsigned SPIN_LIMIT = 1u << 22;

struct Scratch {
    unsigned epoch;
    unsigned pad[31];
    unsigned long long qx[2 * 32 * 64];
    unsigned long long ox[2 * 256 * 8];
    unsigned long long ax[2 * 112 * 8];
    unsigned long long px[16 * 8 * 64];
};

__device__ Scratch g_scratch;

struct Params {
    CUtensorMap wq, k, v, w1, wo, w2;
    const __nv_bfloat16* x;
    const __nv_bfloat16* b1;
    __nv_bfloat16* out;
    Scratch* sc;
};

__device__ __forceinline__ uint32_t smem_u32(const void* p) { return (uint32_t)__cvta_generic_to_shared(p); }
__device__ __forceinline__ void mbar_init(uint32_t bar, uint32_t cnt) {
    asm volatile("mbarrier.init.shared::cta.b64 [%0], %1;" ::"r"(bar), "r"(cnt) : "memory");
}
__device__ __forceinline__ void mbar_expect_tx(uint32_t bar, uint32_t bytes) {
    asm volatile("mbarrier.arrive.expect_tx.shared::cta.b64 _, [%0], %1;" ::"r"(bar), "r"(bytes) : "memory");
}
__device__ __forceinline__ void mbar_arrive(uint32_t bar) {
    asm volatile("mbarrier.arrive.shared::cta.b64 _, [%0];" ::"r"(bar) : "memory");
}
__device__ __forceinline__ void mbar_wait(uint32_t bar) {
    unsigned n = 0;
    uint32_t ok;
    do {
        asm volatile("{\n.reg .pred p;\nmbarrier.try_wait.parity.shared::cta.b64 p, [%1], 0;\nselp.u32 %0, 1, 0, p;\n}"
                     : "=r"(ok) : "r"(bar) : "memory");
    } while (!ok && ++n < SPIN_LIMIT);
}
__device__ __forceinline__ void mbar_wait_cluster(uint32_t bar) {
    unsigned n = 0;
    uint32_t ok;
    do {
        asm volatile("{\n.reg .pred p;\nmbarrier.try_wait.parity.acquire.cluster.shared::cta.b64 p, [%1], 0;\nselp.u32 %0, 1, 0, p;\n}"
                     : "=r"(ok) : "r"(bar) : "memory");
    } while (!ok && ++n < SPIN_LIMIT);
}
__device__ __forceinline__ void tma2d(uint32_t dst, const CUtensorMap* tm, int c0, int c1, uint32_t bar) {
    asm volatile("cp.async.bulk.tensor.2d.shared::cluster.global.mbarrier::complete_tx::bytes [%0], [%1, {%3, %4}], [%2];"
                 ::"r"(dst), "l"((uint64_t)tm), "r"(bar), "r"(c0), "r"(c1) : "memory");
}
__device__ __forceinline__ uint32_t mapa(uint32_t addr, uint32_t rank) {
    uint32_t r;
    asm("mapa.shared::cluster.u32 %0, %1, %2;" : "=r"(r) : "r"(addr), "r"(rank));
    return r;
}
__device__ __forceinline__ void bar_sync(int id, int n) { asm volatile("bar.sync %0, %1;" ::"r"(id), "r"(n) : "memory"); }
__device__ __forceinline__ void bar_arrive(int id, int n) { asm volatile("bar.arrive %0, %1;" ::"r"(id), "r"(n) : "memory"); }

__device__ __forceinline__ void ldsm4(uint32_t (&r)[4], uint32_t addr) {
    asm volatile("ldmatrix.sync.aligned.m8n8.x4.shared.b16 {%0,%1,%2,%3}, [%4];"
                 : "=r"(r[0]), "=r"(r[1]), "=r"(r[2]), "=r"(r[3]) : "r"(addr) : "memory");
}
__device__ __forceinline__ void ldsm4t(uint32_t (&r)[4], uint32_t addr) {
    asm volatile("ldmatrix.sync.aligned.m8n8.x4.trans.shared.b16 {%0,%1,%2,%3}, [%4];"
                 : "=r"(r[0]), "=r"(r[1]), "=r"(r[2]), "=r"(r[3]) : "r"(addr) : "memory");
}
__device__ __forceinline__ void mma16816(float (&c)[4], uint32_t a0, uint32_t a1, uint32_t a2, uint32_t a3, uint32_t b0, uint32_t b1) {
    asm volatile("mma.sync.aligned.m16n8k16.row.col.f32.bf16.bf16.f32 {%0,%1,%2,%3}, {%4,%5,%6,%7}, {%8,%9}, {%0,%1,%2,%3};"
                 : "+f"(c[0]), "+f"(c[1]), "+f"(c[2]), "+f"(c[3])
                 : "r"(a0), "r"(a1), "r"(a2), "r"(a3), "r"(b0), "r"(b1));
}
__device__ __forceinline__ void st_ll1(unsigned long long* p, uint32_t d, uint32_t tag) {
    unsigned long long w = ((unsigned long long)tag << 32) | d;
    asm volatile("st.relaxed.gpu.global.b64 [%0], %1;" ::"l"(p), "l"(w) : "memory");
}
__device__ __forceinline__ void st_ll2(unsigned long long* p, uint32_t d0, uint32_t d1, uint32_t tag) {
    unsigned long long w0 = ((unsigned long long)tag << 32) | d0, w1 = ((unsigned long long)tag << 32) | d1;
    asm volatile("st.relaxed.gpu.global.v2.b64 [%0], {%1, %2};" ::"l"(p), "l"(w0), "l"(w1) : "memory");
}
__device__ __forceinline__ void ld_ll2(const unsigned long long* p, unsigned long long& w0, unsigned long long& w1) {
    asm volatile("ld.relaxed.gpu.global.v2.b64 {%0, %1}, [%2];" : "=l"(w0), "=l"(w1) : "l"(p) : "memory");
}
__device__ __forceinline__ bool tag_ok(unsigned long long w0, unsigned long long w1, uint32_t tag) {
    return (uint32_t)(w0 >> 32) == tag && (uint32_t)(w1 >> 32) == tag;
}
__device__ __forceinline__ float ex2(float x) {
    float y;
    asm("ex2.approx.ftz.f32 %0, %1;" : "=f"(y) : "f"(x));
    return y;
}
__device__ __forceinline__ float bf16r(float x) { return __bfloat162float(__float2bfloat16_rn(x)); }
__device__ __forceinline__ uint32_t pack_bf16(float lo, float hi) {
    __nv_bfloat162 v = __floats2bfloat162_rn(lo, hi);
    return *reinterpret_cast<uint32_t*>(&v);
}
__device__ __forceinline__ float bf_lo(uint32_t u) { return __uint_as_float(u << 16); }
__device__ __forceinline__ float bf_hi(uint32_t u) { return __uint_as_float(u & 0xffff0000u); }
__device__ __forceinline__ float2 lds_f2(uint32_t a) {
    float2 v;
    asm volatile("ld.shared.v2.f32 {%0, %1}, [%2];" : "=f"(v.x), "=f"(v.y) : "r"(a) : "memory");
    return v;
}
__device__ __forceinline__ float lds_f1(uint32_t a) {
    float v;
    asm volatile("ld.shared.f32 %0, [%1];" : "=f"(v) : "r"(a) : "memory");
    return v;
}
__device__ __forceinline__ uint32_t lds_u1(uint32_t a) {
    uint32_t v;
    asm volatile("ld.shared.u32 %0, [%1];" : "=r"(v) : "r"(a) : "memory");
    return v;
}
__device__ __forceinline__ void lds_u4(uint32_t* r, uint32_t a) {
    asm volatile("ld.shared.v4.u32 {%0,%1,%2,%3}, [%4];" : "=r"(r[0]), "=r"(r[1]), "=r"(r[2]), "=r"(r[3]) : "r"(a) : "memory");
}
__device__ __forceinline__ void sts_f1(uint32_t a, float v) { asm volatile("st.shared.f32 [%0], %1;" ::"r"(a), "f"(v) : "memory"); }
__device__ __forceinline__ void sts_u1(uint32_t a, uint32_t v) { asm volatile("st.shared.u32 [%0], %1;" ::"r"(a), "r"(v) : "memory"); }
__device__ __forceinline__ void sts_u4(uint32_t a, uint32_t x, uint32_t y, uint32_t z, uint32_t w) {
    asm volatile("st.shared.v4.u32 [%0], {%1,%2,%3,%4};" ::"r"(a), "r"(x), "r"(y), "r"(z), "r"(w) : "memory");
}

#define TS(i) do { } while (0)

__device__ __forceinline__ void gemv_tile64(float (&acc)[2][4], uint32_t base, int row, int lchk, uint32_t b0, uint32_t b1) {
    uint32_t a0[4], a1[4];
    const uint32_t ra = base + row * 64;
    const int sw = (row >> 1) & 3;
    ldsm4t(a0, ra + ((lchk ^ sw) << 4));
    ldsm4t(a1, ra + (((2 + lchk) ^ sw) << 4));
    mma16816(acc[0], a0[0], a0[1], a0[2], a0[3], b0, b1);
    mma16816(acc[1], a1[0], a1[1], a1[2], a1[3], b0, b1);
}

__global__ void __cluster_dims__(8, 1, 1) __launch_bounds__(NTHREADS, 2) fused_decode_kernel(const __grid_constant__ Params p) {
    extern __shared__ __align__(1024) uint8_t smem[];
    const uint32_t sb = smem_u32(smem);
    const uint32_t bars = sb + SM_BAR;
    const int c = blockIdx.x;
    const int warp = threadIdx.x >> 5, lane = threadIdx.x & 31;
    const int bh = c >> 3, j = c & 7;
    const int r = c >> 4, g16 = c & 15;

    if (warp == NCW) {
        if (lane == 0) {
#pragma unroll
            for (int i = 0; i < 4; i++) mbar_init(bars + i * 8, 1);
            asm volatile("fence.proxy.async.shared::cta;" ::: "memory");
#pragma unroll
            for (int i = 0; i < CH_W1; i++) {
                mbar_expect_tx(bars + i * 8, 8192);
                tma2d(sb + slot_off(i), &p.wq, 32 * c, 128 * i, bars + i * 8);
            }
#pragma unroll
            for (int k = 4; k < NCHUNK; k++) mbar_init(bars + k * 8, 1);
            mbar_init(bars + BAR_EQ * 8, NCW);
#pragma unroll
            for (int k = 0; k < 8; k++) mbar_init(bars + (BAR_EK + k) * 8, 1);
            mbar_init(bars + BAR_EV * 8, NCW);
            asm volatile("fence.proxy.async.shared::cta;" ::: "memory");
        }
        __syncwarp();
        bar_arrive(1, NTHREADS);
        asm volatile("barrier.cluster.arrive.relaxed.aligned;" ::: "memory");
        if (lane == 0) {
            const int krow = bh * SK + WIN0 + j * 256;
#pragma unroll
            for (int i = CH_W1; i < NCHUNK; i++) {
                const uint32_t bar = bars + i * 8;
                const uint32_t dst = sb + slot_off(i);
                if (i >= WINDOW) mbar_wait(bar - WINDOW * 8);
                if (i == NSLOT) mbar_wait(bars + BAR_EQ * 8);
                if (i >= NSLOT + CH_K && i < NSLOT + CH_V) mbar_wait(bars + (BAR_EK + i - NSLOT - CH_K) * 8);
                if (i == NSLOT + CH_V) mbar_wait(bars + BAR_EV * 8);
                if (i < CH_K) {
                    const int q = i - CH_W1;
                    if (c < 112) {
                        mbar_expect_tx(bar, 8192);
                        tma2d(dst, &p.w1, 16 * c, 256 * q, bar);
                    } else {
                        mbar_expect_tx(bar, 0);
                    }
                } else if (i < CH_V) {
                    const int q = i - CH_K;
                    mbar_expect_tx(bar, 8192);
                    tma2d(dst, &p.k, 0, krow + q * 32, bar);
                    tma2d(dst + 4096, &p.k, 64, krow + q * 32, bar);
                } else if (i < CH_WO) {
                    const int q = i - CH_V;
                    mbar_expect_tx(bar, 8192);
                    tma2d(dst, &p.v, 0, krow + q * 32, bar);
                    tma2d(dst + 4096, &p.v, 64, krow + q * 32, bar);
                } else if (i < CH_W2) {
                    const int q = i - CH_WO;
                    mbar_expect_tx(bar, 8192);
                    tma2d(dst, &p.wo, 32 * g16, 512 * r + 128 * q, bar);
                } else {
                    const int q = i - CH_W2;
                    mbar_expect_tx(bar, 7168);
                    tma2d(dst, &p.w2, 32 * g16, 224 * r + 112 * q, bar);
                }
                TS(i);
            }
        }
        return;
    }

    Scratch* const sc = p.sc;
    const float LOG2E = 1.4426950408889634f;

    if (warp == NCW + 1) {
        const uint32_t tag = *reinterpret_cast<volatile unsigned*>(&sc->epoch) + 1u;
        if (lane == 0) {
            mbar_init(bars + BAR_ST * 8, 1);
            mbar_init(bars + BAR_PO * 8, 1);
            asm volatile("fence.mbarrier_init.release.cluster;" ::: "memory");
            mbar_expect_tx(bars + BAR_ST * 8, 256);
            mbar_expect_tx(bars + BAR_PO * 8, 2048);
            sts_u1(sb + SM_EPOCH, tag);
        }
        __syncwarp();
        bar_arrive(1, NTHREADS);
        asm volatile("barrier.cluster.arrive.relaxed.aligned;" ::: "memory");
        TS(0);
        {
            const unsigned long long* src = &sc->qx[((bh >> 3) * 32 + (bh & 7) * 4) * 64 + 2 * lane];
            unsigned pend = 0xf, n = 0;
            while (true) {
                unsigned long long w[4][2];
#pragma unroll
                for (int h = 0; h < 4; h++)
                    if (pend >> h & 1) ld_ll2(src + h * 64, w[h][0], w[h][1]);
#pragma unroll
                for (int h = 0; h < 4; h++)
                    if ((pend >> h & 1) && tag_ok(w[h][0], w[h][1], tag)) {
                        const uint32_t dst = sb + SM_Q + ((h * 4 + ((2 * lane) & 3)) * 16 + (lane >> 1)) * 4;
                        sts_u1(dst, (uint32_t)w[h][0]);
                        sts_u1(dst + 64, (uint32_t)w[h][1]);
                        pend &= ~(1u << h);
                    }
                if (__all_sync(~0u, pend == 0) || ++n >= SPIN_LIMIT) break;
                __nanosleep(100);
            }
        }
        bar_arrive(3, NCT + 32);
        TS(1);
        asm volatile("barrier.cluster.wait.acquire.aligned;" ::: "memory");
        bar_sync(4, NCT + 32);
        {
            float mx = lds_f1(sb + SM_MAX + lane * 4);
            float sm = lds_f1(sb + SM_SUM + lane * 4);
#pragma unroll
            for (int o = 4; o < 32; o <<= 1) { mx = fmaxf(mx, __shfl_xor_sync(~0u, mx, o)); sm += __shfl_xor_sync(~0u, sm, o); }
            const uint32_t dst = mapa(sb + SM_INS + (j * 4 + (lane & 3)) * 8, lane >> 2);
            const uint32_t rbar = mapa(bars + BAR_ST * 8, lane >> 2);
            asm volatile("st.async.weak.shared::cluster.mbarrier::complete_tx::bytes.v2.f32 [%0], {%1, %2}, [%3];"
                         ::"r"(dst), "f"(mx), "f"(sm), "r"(rbar) : "memory");
        }
        TS(2);
        float coef[8];
        {
            mbar_wait_cluster(bars + BAR_ST * 8);
            const float2 st = lds_f2(sb + SM_INS + lane * 8);
            float gm = st.x;
#pragma unroll
            for (int o = 4; o < 32; o <<= 1) gm = fmaxf(gm, __shfl_xor_sync(~0u, gm, o));
            const float wj = ex2((st.x - gm) * LOG2E);
            float gl = wj * st.y;
#pragma unroll
            for (int o = 4; o < 32; o <<= 1) gl += __shfl_xor_sync(~0u, gl, o);
            const float cj = wj / gl;
#pragma unroll
            for (int k = 0; k < 8; k++) coef[k] = __shfl_sync(~0u, cj, k * 4 + (lane >> 3));
        }
        TS(3);
        mbar_wait_cluster(bars + BAR_PO * 8);
        {
            float o0 = 0.f, o1 = 0.f;
#pragma unroll
            for (int k = 0; k < 8; k++) {
                const float2 v = lds_f2(sb + SM_INB + k * 256 + lane * 8);
                o0 = fmaf(coef[k], v.x, o0);
                o1 = fmaf(coef[k], v.y, o1);
            }
            const int head = (bh & 7) * 4 + (lane >> 3);
            st_ll1(&sc->ox[((bh >> 3) * 256 + head * 8 + j) * 8 + (lane & 7)], pack_bf16(o0, o1), tag);
        }
        TS(4);
        return;
    }

    const int u = warp;
    const int fg = lane >> 2, ft = lane & 3;
    asm volatile("barrier.cluster.arrive.relaxed.aligned;" ::: "memory");

    uint32_t xres = 0;
    uint32_t b1pair = 0;
    if (u < 2) {
        const uint4* x4 = reinterpret_cast<const uint4*>(p.x) + u * 64 + lane * 2;
        const uint4 v0 = __ldg(x4), v1 = __ldg(x4 + 1);
        if (u == 0) xres = __ldg(reinterpret_cast<const uint32_t*>(p.x) + (lane >> 4) * 256 + g16 * 16 + (lane & 15));
        if (u == 1 && c < 112) b1pair = __ldg(reinterpret_cast<const uint32_t*>(p.b1) + c * 8 + (lane & 7));
        const uint32_t a[8] = {v0.x, v0.y, v0.z, v0.w, v1.x, v1.y, v1.z, v1.w};
        float s0 = 0.f;
#pragma unroll
        for (int i = 0; i < 8; i++) s0 += bf_lo(a[i]) + bf_hi(a[i]);
#pragma unroll
        for (int o = 16; o > 0; o >>= 1) s0 += __shfl_xor_sync(~0u, s0, o);
        const float m0 = s0 * (1.f / D_MODEL);
        float q0 = 0.f;
#pragma unroll
        for (int i = 0; i < 8; i++) {
            float d;
            d = bf_lo(a[i]) - m0; q0 += d * d; d = bf_hi(a[i]) - m0; q0 += d * d;
        }
#pragma unroll
        for (int o = 16; o > 0; o >>= 1) q0 += __shfl_xor_sync(~0u, q0, o);
        const float mean = bf16r(m0);
        const float var = bf16r(q0 * (1.f / D_MODEL));
        const float den = bf16r(sqrtf(bf16r(var + 1e-5f)));
        const float rden = 1.f / den;
        uint32_t o[8];
#pragma unroll
        for (int i = 0; i < 8; i++) o[i] = pack_bf16(bf16r(bf_lo(a[i]) - mean) * rden, bf16r(bf_hi(a[i]) - mean) * rden);
        const uint32_t dst = sb + SM_XN + u * 1024 + lane * 32;
        sts_u4(dst, o[0], o[1], o[2], o[3]);
        sts_u4(dst + 16, o[4], o[5], o[6], o[7]);
        TS(0);
    }

    const int lrow = (lane & 7) + ((lane >> 4) << 3);
    const int lchk = (lane >> 3) & 1;

    bar_sync(1, NTHREADS);
    const uint32_t tag = lds_u1(sb + SM_EPOCH);
    uint32_t xb[4][2];
#pragma unroll
    for (int q = 0; q < 4; q++) {
        xb[q][0] = lds_u1(sb + SM_XN + (fg & 1) * 1024 + (q * 64 + u * 8 + ft) * 4);
        xb[q][1] = lds_u1(sb + SM_XN + (fg & 1) * 1024 + (q * 64 + u * 8 + 4 + ft) * 4);
    }

    {
        float acc[2][4] = {};
#pragma unroll
        for (int q = 0; q < 4; q++) {
            mbar_wait(bars + (CH_WQ + q) * 8);
            gemv_tile64(acc, sb + slot_off(CH_WQ + q), u * 16 + lrow, lchk, xb[q][0], xb[q][1]);
        }
        TS(1);
        if (ft == 0) {
            const uint32_t rb = sb + SM_REDA + u * 256;
#pragma unroll
            for (int mt = 0; mt < 2; mt++) {
                sts_f1(rb + (mt * 16 + fg) * 4, acc[mt][0]);
                sts_f1(rb + 128 + (mt * 16 + fg) * 4, acc[mt][1]);
                sts_f1(rb + (mt * 16 + fg + 8) * 4, acc[mt][2]);
                sts_f1(rb + 128 + (mt * 16 + fg + 8) * 4, acc[mt][3]);
            }
        }
    }
    bar_sync(2, NCT);
    if (u == 0) {
        float2 s = make_float2(0.f, 0.f);
#pragma unroll
        for (int w = 0; w < NCW; w++) {
            float2 v = lds_f2(sb + SM_REDA + w * 256 + lane * 8);
            s.x += v.x; s.y += v.y;
        }
        st_ll1(&sc->qx[((lane >> 4) * 32 + (c >> 2)) * 64 + (c & 3) * 16 + (lane & 15)], pack_bf16(s.x, s.y), tag);
        TS(2);
    }
    if (c < 112) {
        float acc[4] = {};
#pragma unroll
        for (int q = 0; q < 4; q++) {
            if ((q & 1) == 0) mbar_wait(bars + (CH_W1 + (q >> 1)) * 8);
            const int row = (q & 1) * 128 + u * 16 + lrow;
            uint32_t a[4];
            ldsm4t(a, sb + slot_off(CH_W1 + (q >> 1)) + row * 32 + ((lchk ^ ((row >> 2) & 1)) << 4));
            mma16816(acc, a[0], a[1], a[2], a[3], xb[q][0], xb[q][1]);
        }
        TS(10);
        if (lane == 0) mbar_arrive(bars + BAR_EQ * 8);
        if (ft == 0) {
            const uint32_t rb = sb + SM_REDB + u * 128;
            sts_f1(rb + fg * 4, acc[0]);
            sts_f1(rb + 64 + fg * 4, acc[1]);
            sts_f1(rb + (fg + 8) * 4, acc[2]);
            sts_f1(rb + 64 + (fg + 8) * 4, acc[3]);
        }
        bar_sync(2, NCT);
        if (u == 1 && lane < 16) {
            float2 s = make_float2(0.f, 0.f);
#pragma unroll
            for (int k = 0; k < NCW; k++) {
                float2 v = lds_f2(sb + SM_REDB + k * 128 + lane * 8);
                s.x += v.x; s.y += v.y;
            }
            float h[2] = {bf16r(bf16r(s.x) + bf_lo(b1pair)), bf16r(bf16r(s.y) + bf_hi(b1pair))};
            float a[2];
#pragma unroll
            for (int i = 0; i < 2; i++) {
                const float e = bf16r(__expf(-fabsf(h[i])));
                const float sp = bf16r(bf16r(log1pf(e)) + fmaxf(h[i], 0.f));
                a[i] = h[i] * bf16r(tanhf(sp));
            }
            const int dp = lane & 7;
            st_ll1(&sc->ax[(((lane >> 3) * 112 + c) * 4 + (dp & 3)) * 2 + (dp >> 2)], pack_bf16(a[0], a[1]), tag);
            TS(11);
        }
    } else {
        if (lane == 0) mbar_arrive(bars + BAR_EQ * 8);
    }

    asm volatile("barrier.cluster.wait.acquire.aligned;" ::: "memory");
    bar_sync(3, NCT + 32);
    TS(3);

    {
        uint32_t qa[16];
#pragma unroll
        for (int i = 0; i < 4; i++) lds_u4(qa + 4 * i, sb + SM_Q + ((fg & 3) * 4 + ft) * 64 + i * 16);
        mbar_wait(bars + (CH_K + u) * 8);
        TS(4);
        float acc[4][4] = {};
        const uint32_t kb = sb + ((CH_K + u) % NSLOT) * 8192 + (lane & 7) * 128;
#pragma unroll
        for (int q = 0; q < 4; q++) {
            const int chunk = q * 4 + (lane >> 3);
            const uint32_t off = (chunk >> 3) * 4096 + (((chunk & 7) ^ (lane & 7)) << 4);
#pragma unroll
            for (int nt = 0; nt < 4; nt++) {
                uint32_t b[4];
                ldsm4(b, kb + nt * 1024 + off);
                mma16816(acc[nt], qa[4 * q], 0u, qa[4 * q + 1], 0u, b[0], b[1]);
                mma16816(acc[nt], qa[4 * q + 2], 0u, qa[4 * q + 3], 0u, b[2], b[3]);
            }
        }
        if (lane == 0) mbar_arrive(bars + (BAR_EK + u) * 8);
        const float scale = 0.08838834764831845f;
        float sv[8];
#pragma unroll
        for (int i = 0; i < 8; i++) sv[i] = bf16r(bf16r(acc[i >> 1][i & 1]) * scale);
        float m = fmaxf(fmaxf(fmaxf(sv[0], sv[1]), fmaxf(sv[2], sv[3])), fmaxf(fmaxf(sv[4], sv[5]), fmaxf(sv[6], sv[7])));
        m = fmaxf(m, __shfl_xor_sync(~0u, m, 1));
        m = fmaxf(m, __shfl_xor_sync(~0u, m, 2));
        if (lane < 16 && ft == 0) sts_f1(sb + SM_MAX + (u * 4 + fg) * 4, m);
        TS(5);
        bar_sync(2, NCT);
        m = lds_f1(sb + SM_MAX + ((ft + 4 * (fg >> 2)) * 4 + (fg & 3)) * 4);
        m = fmaxf(m, __shfl_xor_sync(~0u, m, 1));
        m = fmaxf(m, __shfl_xor_sync(~0u, m, 2));
        m = fmaxf(m, __shfl_xor_sync(~0u, m, 16));
#pragma unroll
        for (int i = 0; i < 8; i++) sv[i] = ex2((sv[i] - m) * LOG2E);
        float l = ((sv[0] + sv[1]) + (sv[2] + sv[3])) + ((sv[4] + sv[5]) + (sv[6] + sv[7]));
        l += __shfl_xor_sync(~0u, l, 1);
        l += __shfl_xor_sync(~0u, l, 2);
        if (lane < 16) {
            sts_u4(sb + SM_P + (u * 16 + lane) * 16, pack_bf16(sv[0], sv[1]), pack_bf16(sv[2], sv[3]), pack_bf16(sv[4], sv[5]),
                   pack_bf16(sv[6], sv[7]));
            if (ft == 0) sts_f1(sb + SM_SUM + (u * 4 + fg) * 4, l);
        }
        bar_sync(4, NCT + 32);
        TS(6);
    }

    unsigned long long w[6][2] = {};
    const unsigned long long* so = &sc->ox[(((fg & 1) * 256 + r * 32 + u) * 4 + ft) * 2];
    const unsigned long long* sa = &sc->ax[(((fg & 1) * 112 + r * 14 + (u < 7 ? u : 0)) * 4 + ft) * 2];
    {
        float acc[2][4] = {};
        const uint32_t voff = (u >> 2) * 4096 + lane * 128;
        const uint32_t c0 = (((u & 3) * 2) ^ (lane & 7)) << 4, c1 = (((u & 3) * 2 + 1) ^ (lane & 7)) << 4;
#pragma unroll
        for (int i = 0; i < 8; i++) {
            uint32_t pa[4], b0[4], b1[4];
            lds_u4(pa, sb + SM_P + (i * 16 + (lane & 15)) * 16);
            mbar_wait(bars + (CH_V + i) * 8);
            ldsm4t(b0, sb + slot_off(CH_V + i) + voff + c0);
            ldsm4t(b1, sb + slot_off(CH_V + i) + voff + c1);
            mma16816(acc[0], pa[0], 0u, pa[1], 0u, b0[0], b0[1]);
            mma16816(acc[1], pa[0], 0u, pa[1], 0u, b1[0], b1[1]);
            mma16816(acc[0], pa[2], 0u, pa[3], 0u, b0[2], b0[3]);
            mma16816(acc[1], pa[2], 0u, pa[3], 0u, b1[2], b1[3]);
            if (i == 0 && lane == 0) mbar_arrive(bars + BAR_EV * 8);
        }
        TS(8);
        if (lane < 16) {
            const uint32_t dst = mapa(sb + SM_INB + j * 256 + lane * 16, u);
            const uint32_t rbar = mapa(bars + BAR_PO * 8, u);
            asm volatile("st.async.weak.shared::cluster.mbarrier::complete_tx::bytes.v4.f32 [%0], {%1, %2, %3, %4}, [%5];"
                         ::"r"(dst), "f"(acc[0][0]), "f"(acc[0][1]), "f"(acc[1][0]), "f"(acc[1][1]), "r"(rbar) : "memory");
        }
        TS(9);
    }

    {
        unsigned long long v[7][2] = {};
        const unsigned long long* psrc = &sc->px[(g16 * 8 + 1) * 64 + lane * 2];
        if (u == 0 && r == 0) {
#pragma unroll
            for (int i = 0; i < 7; i++) ld_ll2(psrc + i * 64, v[i][0], v[i][1]);
        }
        uint32_t wa[4][2][4];
        const int row = u * 16 + lrow;
        const uint32_t ro0 = row * 64 + ((lchk ^ ((row >> 1) & 3)) << 4), ro1 = row * 64 + (((2 + lchk) ^ ((row >> 1) & 3)) << 4);
        auto poll = [&](int lo, int hi) {
            if (lane < 8) {
                unsigned n = 0;
                while (true) {
#pragma unroll
                    for (int q = 0; q < 6; q++)
                        if (q >= lo && q < hi && !tag_ok(w[q][0], w[q][1], tag))
                            ld_ll2(q < 4 ? so + q * 64 : sa + (q - 4) * 56, w[q][0], w[q][1]);
                    bool ok = true;
#pragma unroll
                    for (int q = 0; q < 6; q++)
                        if (q >= lo && q < hi) ok = ok && tag_ok(w[q][0], w[q][1], tag);
                    if (ok || ++n >= SPIN_LIMIT) break;
                    __nanosleep(20);
                }
            }
            __syncwarp();
        };
        poll(4, 6);
#pragma unroll
        for (int q = 0; q < 4; q++) {
            mbar_wait(bars + (CH_WO + q) * 8);
            ldsm4t(wa[q][0], sb + slot_off(CH_WO + q) + ro0);
            ldsm4t(wa[q][1], sb + slot_off(CH_WO + q) + ro1);
        }
        TS(12);
        poll(0, 4);
        TS(13);
        float acc[2][4] = {}, acc2[2][4] = {};
#pragma unroll
        for (int q = 0; q < 4; q += 2) {
#pragma unroll
            for (int mt = 0; mt < 2; mt++) {
                mma16816(acc[mt], wa[q][mt][0], wa[q][mt][1], wa[q][mt][2], wa[q][mt][3], (uint32_t)w[q][0], (uint32_t)w[q][1]);
                mma16816(acc2[mt], wa[q + 1][mt][0], wa[q + 1][mt][1], wa[q + 1][mt][2], wa[q + 1][mt][3], (uint32_t)w[q + 1][0],
                         (uint32_t)w[q + 1][1]);
            }
        }
        if (u < 7) {
            mbar_wait(bars + CH_W2 * 8);
            gemv_tile64(acc, sb + slot_off(CH_W2), row, lchk, (uint32_t)w[4][0], (uint32_t)w[4][1]);
            mbar_wait(bars + (CH_W2 + 1) * 8);
            gemv_tile64(acc2, sb + slot_off(CH_W2 + 1), row, lchk, (uint32_t)w[5][0], (uint32_t)w[5][1]);
        }
#pragma unroll
        for (int mt = 0; mt < 2; mt++)
#pragma unroll
            for (int i = 0; i < 4; i++) acc[mt][i] += acc2[mt][i];
        TS(14);
        if (ft == 0) {
            const uint32_t rb = sb + SM_REDA + u * 256;
#pragma unroll
            for (int mt = 0; mt < 2; mt++) {
                sts_f1(rb + (mt * 16 + fg) * 4, acc[mt][0]);
                sts_f1(rb + 128 + (mt * 16 + fg) * 4, acc[mt][1]);
                sts_f1(rb + (mt * 16 + fg + 8) * 4, acc[mt][2]);
                sts_f1(rb + 128 + (mt * 16 + fg + 8) * 4, acc[mt][3]);
            }
        }
        if (u != 0) { bar_arrive(2, NCT); return; }
        bar_sync(2, NCT);
        float2 s = make_float2(0.f, 0.f);
#pragma unroll
        for (int k = 0; k < NCW; k++) {
            float2 t = lds_f2(sb + SM_REDA + k * 256 + lane * 8);
            s.x += t.x; s.y += t.y;
        }
        if (r != 0) {
            st_ll2(&sc->px[(g16 * 8 + r) * 64 + lane * 2], __float_as_uint(s.x), __float_as_uint(s.y), tag);
            TS(15);
            return;
        }
        TS(15);
        unsigned n = 0;
        while (true) {
#pragma unroll
            for (int i = 0; i < 7; i++)
                if (!tag_ok(v[i][0], v[i][1], tag)) ld_ll2(psrc + i * 64, v[i][0], v[i][1]);
            bool ok = true;
#pragma unroll
            for (int i = 0; i < 7; i++) ok = ok && tag_ok(v[i][0], v[i][1], tag);
            if (ok || ++n >= SPIN_LIMIT) break;
        }
#pragma unroll
        for (int i = 0; i < 7; i++) { s.x += __uint_as_float((uint32_t)v[i][0]); s.y += __uint_as_float((uint32_t)v[i][1]); }
        reinterpret_cast<uint32_t*>(p.out)[(lane >> 4) * 256 + g16 * 16 + (lane & 15)] =
            pack_bf16(bf_lo(xres) + s.x, bf_hi(xres) + s.y);
        __syncwarp();
        if (c == 0 && lane == 0) sc->epoch = tag;
        TS(16);
    }
}

typedef CUresult (*EncodeTiledFn)(CUtensorMap*, CUtensorMapDataType, cuuint32_t, void*, const cuuint64_t*, const cuuint64_t*,
                                  const cuuint32_t*, const cuuint32_t*, CUtensorMapInterleave, CUtensorMapSwizzle,
                                  CUtensorMapL2promotion, CUtensorMapFloatOOBfill);

void make_map(EncodeTiledFn enc, CUtensorMap* m, const void* base, uint64_t cols, uint64_t rows, uint32_t box_c, uint32_t box_r,
              CUtensorMapSwizzle sw) {
    cuuint64_t gd[2] = {cols, rows};
    cuuint64_t gs[1] = {cols * 2};
    cuuint32_t bd[2] = {box_c, box_r};
    cuuint32_t es[2] = {1, 1};
    enc(m, CU_TENSOR_MAP_DATA_TYPE_BFLOAT16, 2, const_cast<void*>(base), gd, gs, bd, es, CU_TENSOR_MAP_INTERLEAVE_NONE, sw,
        CU_TENSOR_MAP_L2_PROMOTION_L2_128B, CU_TENSOR_MAP_FLOAT_OOB_FILL_NONE);
}

}

extern "C" void kernel_launch(void* const* d_in, const int* in_sizes, int n_in, void* d_out, int out_size) {
    (void)in_sizes; (void)n_in; (void)out_size;
    static EncodeTiledFn enc = nullptr;
    static Scratch* sc = nullptr;
    if (!enc) {
        void* fn = nullptr;
        cudaDriverEntryPointQueryResult st;
        cudaGetDriverEntryPoint("cuTensorMapEncodeTiled", &fn, cudaEnableDefault, &st);
        enc = (EncodeTiledFn)fn;
        cudaFuncSetAttribute(fused_decode_kernel, cudaFuncAttributeMaxDynamicSharedMemorySize, SM_TOTAL);
        void* sp = nullptr;
        cudaGetSymbolAddress(&sp, g_scratch);
        sc = (Scratch*)sp;
    }
    Params p;
    make_map(enc, &p.k, d_in[1], 128, 2 * 8 * SK, 64, 32, CU_TENSOR_MAP_SWIZZLE_128B);
    make_map(enc, &p.v, d_in[2], 128, 2 * 8 * SK, 64, 32, CU_TENSOR_MAP_SWIZZLE_128B);
    make_map(enc, &p.wq, d_in[3], 4096, 512, 32, 128, CU_TENSOR_MAP_SWIZZLE_64B);
    make_map(enc, &p.wo, d_in[4], 512, 4096, 32, 128, CU_TENSOR_MAP_SWIZZLE_64B);
    make_map(enc, &p.w1, d_in[6], FF, 512, 16, 256, CU_TENSOR_MAP_SWIZZLE_32B);
    make_map(enc, &p.w2, d_in[8], 512, FF, 32, 112, CU_TENSOR_MAP_SWIZZLE_64B);
    p.x = (const __nv_bfloat16*)d_in[0];
    p.b1 = (const __nv_bfloat16*)d_in[7];
    p.out = (__nv_bfloat16*)d_out;
    p.sc = sc;
    fused_decode_kernel<<<NCTA, NTHREADS, SM_TOTAL, cudaStreamPerThread>>>(p);
}
```

```cpp
#include <cuda_runtime.h>
#include <cuda_bf16.h>
#include <cuda.h>
#include <stdint.h>

namespace {

constexpr int D_MODEL = 512;
constexpr int SK = 8192;
constexpr int WIN = 2048;
constexpr int WIN0 = SK - WIN;
constexpr int FF = 1792;

constexpr int NCTA = 128;
constexpr int NCW = 8;
constexpr int NCT = NCW * 32;
constexpr int NTHREADS = (NCW + 2) * 32;

constexpr int CH_WQ = 0, CH_W1 = 4, CH_K = 6, CH_V = 14, CH_WO = 22, CH_W2 = 26, NCHUNK = 28;
constexpr int NSLOT = 13;
#define WINDOW 6
__host__ __device__ constexpr int slot_off(int chunk) { return (chunk % NSLOT) * 8192; }

constexpr int BAR_FULL = 0;
constexpr int BAR_EQ = NCHUNK;
constexpr int BAR_EK = BAR_EQ + 1;
constexpr int BAR_EV = BAR_EK + 8;
constexpr int BAR_ST = BAR_EV + 1;
constexpr int BAR_PO = BAR_ST + 1;
constexpr int NBAR = BAR_PO + 1;

constexpr int SM_RING = 0;
constexpr int SM_INB = NSLOT * 8192;
constexpr int SM_INS = SM_INB + 2048;
constexpr int SM_REDA = SM_INB;
constexpr int SM_XN = SM_INS + 256;
constexpr int SM_REDB = SM_XN + 2048;
constexpr int SM_P = SM_XN;
constexpr int SM_Q = SM_XN + 4096;
constexpr int SM_REDO = SM_Q;
constexpr int SM_MAX = SM_Q + 2048;
constexpr int SM_SUM = SM_MAX + 128;
constexpr int SM_BAR = SM_SUM + 128;
constexpr int SM_EPOCH = SM_BAR + NBAR * 8;
constexpr int SM_TOTAL = SM_EPOCH + 16;
static_assert(SM_TOTAL <= 115712, "two CTAs must fit on one SM");

constexpr unsigned SPIN_LIMIT = 1u << 22;

struct Scratch {
    unsigned epoch;
    unsigned pad[31];
    unsigned long long qx[2 * 32 * 64];
    unsigned long long ox[2 * 256 * 8];
    unsigned long long ax[2 * 112 * 8];
    unsigned long long px[16 * 8 * 64];
};

__device__ Scratch g_scratch;

struct Params {
    CUtensorMap wq, k, v, w1, wo, w2;
    const __nv_bfloat16* x;
    const __nv_bfloat16* b1;
    __nv_bfloat16* out;
    Scratch* sc;
};

__device__ __forceinline__ uint32_t smem_u32(const void* p) { return (uint32_t)__cvta_generic_to_shared(p); }
__device__ __forceinline__ void mbar_init(uint32_t bar, uint32_t cnt) {
    asm volatile("mbarrier.init.shared::cta.b64 [%0], %1;" ::"r"(bar), "r"(cnt) : "memory");
}
__device__ __forceinline__ void mbar_expect_tx(uint32_t bar, uint32_t bytes) {
    asm volatile("mbarrier.arrive.expect_tx.shared::cta.b64 _, [%0], %1;" ::"r"(bar), "r"(bytes) : "memory");
}
__device__ __forceinline__ void mbar_arrive(uint32_t bar) {
    asm volatile("mbarrier.arrive.shared::cta.b64 _, [%0];" ::"r"(bar) : "memory");
}
__device__ __forceinline__ void mbar_wait(uint32_t bar) {
    unsigned n = 0;
    uint32_t ok;
    do {
        asm volatile("{\n.reg .pred p;\nmbarrier.try_wait.parity.shared::cta.b64 p, [%1], 0;\nselp.u32 %0, 1, 0, p;\n}"
                     : "=r"(ok) : "r"(bar) : "memory");
    } while (!ok && ++n < SPIN_LIMIT);
}
__device__ __forceinline__ void mbar_wait_cluster(uint32_t bar) {
    unsigned n = 0;
    uint32_t ok;
    do {
        asm volatile("{\n.reg .pred p;\nmbarrier.try_wait.parity.acquire.cluster.shared::cta.b64 p, [%1], 0;\nselp.u32 %0, 1, 0, p;\n}"
                     : "=r"(ok) : "r"(bar) : "memory");
    } while (!ok && ++n < SPIN_LIMIT);
}
__device__ __forceinline__ void tma2d(uint32_t dst, const CUtensorMap* tm, int c0, int c1, uint32_t bar) {
    asm volatile("cp.async.bulk.tensor.2d.shared::cluster.global.mbarrier::complete_tx::bytes [%0], [%1, {%3, %4}], [%2];"
                 ::"r"(dst), "l"((uint64_t)tm), "r"(bar), "r"(c0), "r"(c1) : "memory");
}
__device__ __forceinline__ uint32_t mapa(uint32_t addr, uint32_t rank) {
    uint32_t r;
    asm("mapa.shared::cluster.u32 %0, %1, %2;" : "=r"(r) : "r"(addr), "r"(rank));
    return r;
}
__device__ __forceinline__ void bar_sync(int id, int n) { asm volatile("bar.sync %0, %1;" ::"r"(id), "r"(n) : "memory"); }
__device__ __forceinline__ void bar_arrive(int id, int n) { asm volatile("bar.arrive %0, %1;" ::"r"(id), "r"(n) : "memory"); }

__device__ __forceinline__ void ldsm4(uint32_t (&r)[4], uint32_t addr) {
    asm volatile("ldmatrix.sync.aligned.m8n8.x4.shared.b16 {%0,%1,%2,%3}, [%4];"
                 : "=r"(r[0]), "=r"(r[1]), "=r"(r[2]), "=r"(r[3]) : "r"(addr) : "memory");
}
__device__ __forceinline__ void ldsm4t(uint32_t (&r)[4], uint32_t addr) {
    asm volatile("ldmatrix.sync.aligned.m8n8.x4.trans.shared.b16 {%0,%1,%2,%3}, [%4];"
                 : "=r"(r[0]), "=r"(r[1]), "=r"(r[2]), "=r"(r[3]) : "r"(addr) : "memory");
}
__device__ __forceinline__ void mma16816(float (&c)[4], uint32_t a0, uint32_t a1, uint32_t a2, uint32_t a3, uint32_t b0, uint32_t b1) {
    asm volatile("mma.sync.aligned.m16n8k16.row.col.f32.bf16.bf16.f32 {%0,%1,%2,%3}, {%4,%5,%6,%7}, {%8,%9}, {%0,%1,%2,%3};"
                 : "+f"(c[0]), "+f"(c[1]), "+f"(c[2]), "+f"(c[3])
                 : "r"(a0), "r"(a1), "r"(a2), "r"(a3), "r"(b0), "r"(b1));
}
__device__ __forceinline__ void st_ll1(unsigned long long* p, uint32_t d, uint32_t tag) {
    unsigned long long w = ((unsigned long long)tag << 32) | d;
    asm volatile("st.relaxed.gpu.global.b64 [%0], %1;" ::"l"(p), "l"(w) : "memory");
}
__device__ __forceinline__ void st_ll2(unsigned long long* p, uint32_t d0, uint32_t d1, uint32_t tag) {
    unsigned long long w0 = ((unsigned long long)tag << 32) | d0, w1 = ((unsigned long long)tag << 32) | d1;
    asm volatile("st.relaxed.gpu.global.v2.b64 [%0], {%1, %2};" ::"l"(p), "l"(w0), "l"(w1) : "memory");
}
__device__ __forceinline__ void ld_ll2(const unsigned long long* p, unsigned long long& w0, unsigned long long& w1) {
    asm volatile("ld.relaxed.gpu.global.v2.b64 {%0, %1}, [%2];" : "=l"(w0), "=l"(w1) : "l"(p) : "memory");
}
__device__ __forceinline__ bool tag_ok(unsigned long long w0, unsigned long long w1, uint32_t tag) {
    return (uint32_t)(w0 >> 32) == tag && (uint32_t)(w1 >> 32) == tag;
}
__device__ __forceinline__ float ex2(float x) {
    float y;
    asm("ex2.approx.ftz.f32 %0, %1;" : "=f"(y) : "f"(x));
    return y;
}
__device__ __forceinline__ float bf16r(float x) { return __bfloat162float(__float2bfloat16_rn(x)); }
__device__ __forceinline__ uint32_t pack_bf16(float lo, float hi) {
    __nv_bfloat162 v = __floats2bfloat162_rn(lo, hi);
    return *reinterpret_cast<uint32_t*>(&v);
}
__device__ __forceinline__ float bf_lo(uint32_t u) { return __uint_as_float(u << 16); }
__device__ __forceinline__ float bf_hi(uint32_t u) { return __uint_as_float(u & 0xffff0000u); }
__device__ __forceinline__ float2 lds_f2(uint32_t a) {
    float2 v;
    asm volatile("ld.shared.v2.f32 {%0, %1}, [%2];" : "=f"(v.x), "=f"(v.y) : "r"(a) : "memory");
    return v;
}
__device__ __forceinline__ float lds_f1(uint32_t a) {
    float v;
    asm volatile("ld.shared.f32 %0, [%1];" : "=f"(v) : "r"(a) : "memory");
    return v;
}
__device__ __forceinline__ uint32_t lds_u1(uint32_t a) {
    uint32_t v;
    asm volatile("ld.shared.u32 %0, [%1];" : "=r"(v) : "r"(a) : "memory");
    return v;
}
__device__ __forceinline__ void lds_u4(uint32_t* r, uint32_t a) {
    asm volatile("ld.shared.v4.u32 {%0,%1,%2,%3}, [%4];" : "=r"(r[0]), "=r"(r[1]), "=r"(r[2]), "=r"(r[3]) : "r"(a) : "memory");
}
__device__ __forceinline__ float4 lds_f4(uint32_t a) {
    float4 v;
    asm volatile("ld.shared.v4.f32 {%0,%1,%2,%3}, [%4];" : "=f"(v.x), "=f"(v.y), "=f"(v.z), "=f"(v.w) : "r"(a) : "memory");
    return v;
}
__device__ __forceinline__ void sts_f2(uint32_t a, float x, float y) {
    asm volatile("st.shared.v2.f32 [%0], {%1, %2};" ::"r"(a), "f"(x), "f"(y) : "memory");
}
__device__ __forceinline__ void sts_f4(uint32_t a, float x, float y, float z, float w) {
    asm volatile("st.shared.v4.f32 [%0], {%1,%2,%3,%4};" ::"r"(a), "f"(x), "f"(y), "f"(z), "f"(w) : "memory");
}
template <int N>
__device__ __forceinline__ void halve(float (&v)[N], int n, int mask, int lane) {
    const bool up = lane & mask;
#pragma unroll
    for (int i = 0; i < N / 2; i++)
        if (i < n / 2) {
            const float keep = up ? v[i + n / 2] : v[i], send = up ? v[i] : v[i + n / 2];
            v[i] = keep + __shfl_xor_sync(~0u, send, mask);
        }
}
__device__ __forceinline__ float warp_max(float x) {
    int i = __float_as_int(x);
    i ^= (i >> 31) & 0x7fffffff;
    i = __reduce_max_sync(~0u, i);
    i ^= (i >> 31) & 0x7fffffff;
    return __int_as_float(i);
}
__device__ __forceinline__ void gemv_piece(float (&acc)[16], uint32_t waddr, uint32_t xaddr) {
    uint32_t w[4];
    lds_u4(w, waddr);
    const uint32_t xw = lds_u1(xaddr);
    const float x0 = bf_lo(xw), x1 = bf_hi(xw);
#pragma unroll
    for (int i = 0; i < 4; i++) {
        const float lo = bf_lo(w[i]), hi = bf_hi(w[i]);
        acc[2 * i] = fmaf(x0, lo, acc[2 * i]);
        acc[2 * i + 1] = fmaf(x0, hi, acc[2 * i + 1]);
        acc[8 + 2 * i] = fmaf(x1, lo, acc[8 + 2 * i]);
        acc[8 + 2 * i + 1] = fmaf(x1, hi, acc[8 + 2 * i + 1]);
    }
}
__device__ __forceinline__ void sts_f1(uint32_t a, float v) { asm volatile("st.shared.f32 [%0], %1;" ::"r"(a), "f"(v) : "memory"); }
__device__ __forceinline__ void sts_u1(uint32_t a, uint32_t v) { asm volatile("st.shared.u32 [%0], %1;" ::"r"(a), "r"(v) : "memory"); }
__device__ __forceinline__ void sts_u4(uint32_t a, uint32_t x, uint32_t y, uint32_t z, uint32_t w) {
    asm volatile("st.shared.v4.u32 [%0], {%1,%2,%3,%4};" ::"r"(a), "r"(x), "r"(y), "r"(z), "r"(w) : "memory");
}

#define TS(i) do { } while (0)

__device__ __forceinline__ void gemv_tile64(float (&acc)[2][4], uint32_t base, int row, int lchk, uint32_t b0, uint32_t b1) {
    uint32_t a0[4], a1[4];
    const uint32_t ra = base + row * 64;
    const int sw = (row >> 1) & 3;
    ldsm4t(a0, ra + ((lchk ^ sw) << 4));
    ldsm4t(a1, ra + (((2 + lchk) ^ sw) << 4));
    mma16816(acc[0], a0[0], a0[1], a0[2], a0[3], b0, b1);
    mma16816(acc[1], a1[0], a1[1], a1[2], a1[3], b0, b1);
}

__global__ void __cluster_dims__(8, 1, 1) __launch_bounds__(NTHREADS, 2) fused_decode_kernel(const __grid_constant__ Params p) {
    extern __shared__ __align__(1024) uint8_t smem[];
    const uint32_t sb = smem_u32(smem);
    const uint32_t bars = sb + SM_BAR;
    const int c = blockIdx.x;
    const int warp = threadIdx.x >> 5, lane = threadIdx.x & 31;
    const int bh = c >> 3, j = c & 7;
    const int r = c >> 4, g16 = c & 15;

    if (warp == NCW) {
        if (lane == 0) {
#pragma unroll
            for (int i = 0; i < 4; i++) mbar_init(bars + i * 8, 1);
            asm volatile("fence.proxy.async.shared::cta;" ::: "memory");
#pragma unroll
            for (int i = 0; i < CH_W1; i++) {
                mbar_expect_tx(bars + i * 8, 8192);
                tma2d(sb + slot_off(i), &p.wq, 32 * c, 128 * i, bars + i * 8);
            }
#pragma unroll
            for (int k = 4; k < NCHUNK; k++) mbar_init(bars + k * 8, 1);
            mbar_init(bars + BAR_EQ * 8, NCW);
#pragma unroll
            for (int k = 0; k < 8; k++) mbar_init(bars + (BAR_EK + k) * 8, 1);
            mbar_init(bars + BAR_EV * 8, NCW);
            asm volatile("fence.proxy.async.shared::cta;" ::: "memory");
        }
        __syncwarp();
        bar_arrive(1, NTHREADS);
        asm volatile("barrier.cluster.arrive.relaxed.aligned;" ::: "memory");
        if (lane == 0) {
            const int krow = bh * SK + WIN0 + j * 256;
#pragma unroll
            for (int i = CH_W1; i < NCHUNK; i++) {
                const uint32_t bar = bars + i * 8;
                const uint32_t dst = sb + slot_off(i);
                if (i >= WINDOW) mbar_wait(bar - WINDOW * 8);
                if (i == NSLOT) mbar_wait(bars + BAR_EQ * 8);
                if (i >= NSLOT + CH_K && i < NSLOT + CH_V) mbar_wait(bars + (BAR_EK + i - NSLOT - CH_K) * 8);
                if (i == NSLOT + CH_V) mbar_wait(bars + BAR_EV * 8);
                if (i < CH_K) {
                    const int q = i - CH_W1;
                    if (c < 112) {
                        mbar_expect_tx(bar, 8192);
                        tma2d(dst, &p.w1, 16 * c, 256 * q, bar);
                    } else {
                        mbar_expect_tx(bar, 0);
                    }
                } else if (i < CH_V) {
                    const int q = i - CH_K;
                    mbar_expect_tx(bar, 8192);
                    tma2d(dst, &p.k, 0, krow + q * 32, bar);
                    tma2d(dst + 4096, &p.k, 64, krow + q * 32, bar);
                } else if (i < CH_WO) {
                    const int q = i - CH_V;
                    mbar_expect_tx(bar, 8192);
                    tma2d(dst, &p.v, 0, krow + q * 32, bar);
                    tma2d(dst + 4096, &p.v, 64, krow + q * 32, bar);
                } else if (i < CH_W2) {
                    const int q = i - CH_WO;
                    mbar_expect_tx(bar, 8192);
                    tma2d(dst, &p.wo, 32 * g16, 512 * r + 128 * q, bar);
                } else {
                    const int q = i - CH_W2;
                    mbar_expect_tx(bar, 7168);
                    tma2d(dst, &p.w2, 32 * g16, 224 * r + 112 * q, bar);
                }
                TS(i);
            }
        }
        return;
    }

    Scratch* const sc = p.sc;
    const float LOG2E = 1.4426950408889634f;

    if (warp == NCW + 1) {
        const uint32_t tag = *reinterpret_cast<volatile unsigned*>(&sc->epoch) + 1u;
        if (lane == 0) {
            mbar_init(bars + BAR_ST * 8, 1);
            mbar_init(bars + BAR_PO * 8, 1);
            asm volatile("fence.mbarrier_init.release.cluster;" ::: "memory");
            mbar_expect_tx(bars + BAR_ST * 8, 256);
            mbar_expect_tx(bars + BAR_PO * 8, 2048);
            sts_u1(sb + SM_EPOCH, tag);
        }
        __syncwarp();
        bar_arrive(1, NTHREADS);
        asm volatile("barrier.cluster.arrive.relaxed.aligned;" ::: "memory");
        TS(0);
        {
            const unsigned long long* src = &sc->qx[((bh >> 3) * 32 + (bh & 7) * 4) * 64 + 2 * lane];
            unsigned pend = 0xf, n = 0;
            while (true) {
                unsigned long long w[4][2];
#pragma unroll
                for (int h = 0; h < 4; h++)
                    if (pend >> h & 1) ld_ll2(src + h * 64, w[h][0], w[h][1]);
#pragma unroll
                for (int h = 0; h < 4; h++)
                    if ((pend >> h & 1) && tag_ok(w[h][0], w[h][1], tag)) {
                        sts_f4(sb + SM_Q + (((lane >> 1) * 4 + h) * 8 + (lane & 1) * 4) * 4, bf_lo((uint32_t)w[h][0]),
                               bf_hi((uint32_t)w[h][0]), bf_lo((uint32_t)w[h][1]), bf_hi((uint32_t)w[h][1]));
                        pend &= ~(1u << h);
                    }
                if (__all_sync(~0u, pend == 0) || ++n >= SPIN_LIMIT) break;
                __nanosleep(100);
            }
        }
        bar_arrive(3, NCT + 32);
        TS(1);
        asm volatile("barrier.cluster.wait.acquire.aligned;" ::: "memory");
        bar_sync(4, NCT + 32);
        {
            float mx = lds_f1(sb + SM_MAX + lane * 4);
            float sm = lds_f1(sb + SM_SUM + lane * 4);
#pragma unroll
            for (int o = 4; o < 32; o <<= 1) { mx = fmaxf(mx, __shfl_xor_sync(~0u, mx, o)); sm += __shfl_xor_sync(~0u, sm, o); }
            const uint32_t dst = mapa(sb + SM_INS + (j * 4 + (lane & 3)) * 8, lane >> 2);
            const uint32_t rbar = mapa(bars + BAR_ST * 8, lane >> 2);
            asm volatile("st.async.weak.shared::cluster.mbarrier::complete_tx::bytes.v2.f32 [%0], {%1, %2}, [%3];"
                         ::"r"(dst), "f"(mx), "f"(sm), "r"(rbar) : "memory");
        }
        TS(2);
        float coef[8];
        {
            mbar_wait_cluster(bars + BAR_ST * 8);
            const float2 st = lds_f2(sb + SM_INS + lane * 8);
            float gm = st.x;
#pragma unroll
            for (int o = 4; o < 32; o <<= 1) gm = fmaxf(gm, __shfl_xor_sync(~0u, gm, o));
            const float wj = ex2((st.x - gm) * LOG2E);
            float gl = wj * st.y;
#pragma unroll
            for (int o = 4; o < 32; o <<= 1) gl += __shfl_xor_sync(~0u, gl, o);
            const float cj = wj / gl;
#pragma unroll
            for (int k = 0; k < 8; k++) coef[k] = __shfl_sync(~0u, cj, k * 4 + (lane >> 3));
        }
        TS(3);
        mbar_wait_cluster(bars + BAR_PO * 8);
        {
            float o0 = 0.f, o1 = 0.f;
#pragma unroll
            for (int k = 0; k < 8; k++) {
                const float2 v = lds_f2(sb + SM_INB + k * 256 + lane * 8);
                o0 = fmaf(coef[k], v.x, o0);
                o1 = fmaf(coef[k], v.y, o1);
            }
            const int head = (bh & 7) * 4 + (lane >> 3);
            st_ll1(&sc->ox[((bh >> 3) * 256 + head * 8 + j) * 8 + (lane & 3) * 2 + ((lane >> 2) & 1)], pack_bf16(o0, o1), tag);
        }
        TS(4);
        return;
    }

    const int u = warp;
    const int fg = lane >> 2, ft = lane & 3;
    asm volatile("barrier.cluster.arrive.relaxed.aligned;" ::: "memory");

    uint32_t xres = 0;
    uint32_t b1pair = 0;
    if (u < 2) {
        const uint4* x4 = reinterpret_cast<const uint4*>(p.x) + u * 64 + lane * 2;
        const uint4 v0 = __ldg(x4), v1 = __ldg(x4 + 1);
        if (u == 0) xres = __ldg(reinterpret_cast<const uint32_t*>(p.x) + (lane >> 4) * 256 + g16 * 16 + (lane & 15));
        if (u == 1 && c < 112) b1pair = __ldg(reinterpret_cast<const uint32_t*>(p.b1) + c * 8 + (lane & 7));
        const uint32_t a[8] = {v0.x, v0.y, v0.z, v0.w, v1.x, v1.y, v1.z, v1.w};
        float s0 = 0.f;
#pragma unroll
        for (int i = 0; i < 8; i++) s0 += bf_lo(a[i]) + bf_hi(a[i]);
#pragma unroll
        for (int o = 16; o > 0; o >>= 1) s0 += __shfl_xor_sync(~0u, s0, o);
        const float m0 = s0 * (1.f / D_MODEL);
        float q0 = 0.f;
#pragma unroll
        for (int i = 0; i < 8; i++) {
            float d;
            d = bf_lo(a[i]) - m0; q0 += d * d; d = bf_hi(a[i]) - m0; q0 += d * d;
        }
#pragma unroll
        for (int o = 16; o > 0; o >>= 1) q0 += __shfl_xor_sync(~0u, q0, o);
        const float mean = bf16r(m0);
        const float var = bf16r(q0 * (1.f / D_MODEL));
        const float den = bf16r(sqrtf(bf16r(var + 1e-5f)));
        const float rden = 1.f / den;
        uint32_t o[8];
#pragma unroll
        for (int i = 0; i < 8; i++) o[i] = pack_bf16(bf16r(bf_lo(a[i]) - mean) * rden, bf16r(bf_hi(a[i]) - mean) * rden);
        const uint32_t dst = sb + SM_XN + lane * 64 + u * 2;
#pragma unroll
        for (int i = 0; i < 8; i++) {
            asm volatile("st.shared.u16 [%0], %1;" ::"r"(dst + i * 8), "h"((unsigned short)(o[i] & 0xffffu)) : "memory");
            asm volatile("st.shared.u16 [%0], %1;" ::"r"(dst + i * 8 + 4), "h"((unsigned short)(o[i] >> 16)) : "memory");
        }
        TS(0);
    }

    const int lrow = (lane & 7) + ((lane >> 4) << 3);
    const int lchk = (lane >> 3) & 1;

    bar_sync(1, NTHREADS);
    const uint32_t tag = lds_u1(sb + SM_EPOCH);

    {
        float acc[16] = {};
#pragma unroll
        for (int q = 0; q < 4; q++) {
            mbar_wait(bars + (CH_WQ + q) * 8);
#pragma unroll
            for (int it = 0; it < 2; it++) {
                const int row = u * 16 + it * 8 + fg;
                gemv_piece(acc, sb + slot_off(CH_WQ + q) + row * 64 + ft * 16, sb + SM_XN + (q * 128 + row) * 4);
            }
        }
        TS(1);
        halve(acc, 16, 16, lane);
        halve(acc, 8, 8, lane);
        halve(acc, 4, 4, lane);
        sts_f2(sb + SM_REDA + u * 256 + ((lane >> 4) * 32 + ft * 8 + ((lane >> 3) & 1) * 4 + ((lane >> 2) & 1) * 2) * 4, acc[0], acc[1]);
    }
    bar_sync(2, NCT);
    if (u == 0) {
        float2 s = make_float2(0.f, 0.f);
#pragma unroll
        for (int w = 0; w < NCW; w++) {
            float2 v = lds_f2(sb + SM_REDA + w * 256 + lane * 8);
            s.x += v.x; s.y += v.y;
        }
        st_ll1(&sc->qx[((lane >> 4) * 32 + (c >> 2)) * 64 + (c & 3) * 16 + (lane & 15)], pack_bf16(s.x, s.y), tag);
        TS(2);
    }

    if (c < 112) {
        float acc[16] = {};
#pragma unroll
        for (int q = 0; q < 2; q++) {
            mbar_wait(bars + (CH_W1 + q) * 8);
#pragma unroll
            for (int it = 0; it < 2; it++) {
                const int row = u * 32 + it * 16 + (lane >> 1);
                gemv_piece(acc, sb + slot_off(CH_W1 + q) + row * 32 + (lane & 1) * 16, sb + SM_XN + (q * 256 + row) * 4);
            }
        }
        TS(10);
        __syncwarp();
        if (lane == 0) mbar_arrive(bars + BAR_EQ * 8);
        halve(acc, 16, 16, lane);
        halve(acc, 8, 8, lane);
        halve(acc, 4, 4, lane);
        halve(acc, 2, 2, lane);
        sts_f1(sb + SM_REDB + u * 128 + ((lane >> 4) * 16 + (lane & 1) * 8 + ((lane >> 1) & 7)) * 4, acc[0]);
        bar_sync(2, NCT);
        if (u == 1 && lane < 16) {
            float2 s = make_float2(0.f, 0.f);
#pragma unroll
            for (int k = 0; k < NCW; k++) {
                float2 v = lds_f2(sb + SM_REDB + k * 128 + lane * 8);
                s.x += v.x; s.y += v.y;
            }
            float h[2] = {bf16r(bf16r(s.x) + bf_lo(b1pair)), bf16r(bf16r(s.y) + bf_hi(b1pair))};
            float a[2];
#pragma unroll
            for (int i = 0; i < 2; i++) {
                const float e = bf16r(__expf(-fabsf(h[i])));
                const float sp = bf16r(bf16r(log1pf(e)) + fmaxf(h[i], 0.f));
                a[i] = h[i] * bf16r(tanhf(sp));
            }
            const int dp = lane & 7;
            st_ll1(&sc->ax[(((lane >> 3) * 112 + c) * 4 + (dp & 3)) * 2 + (dp >> 2)], pack_bf16(a[0], a[1]), tag);
            TS(11);
        }
    } else {
        __syncwarp();
        if (lane == 0) mbar_arrive(bars + BAR_EQ * 8);
    }
    bar_sync(3, NCT + 32);
    TS(3);

    {
        mbar_wait(bars + (CH_K + u) * 8);
        TS(4);
        float sv[4] = {0.f, 0.f, 0.f, 0.f};
        const uint32_t kb = sb + ((CH_K + u) % NSLOT) * 8192 + lane * 128;
#pragma unroll
        for (int ch = 0; ch < 16; ch++) {
            uint32_t k[4];
            lds_u4(k, kb + (ch >> 3) * 4096 + (((ch & 7) ^ (lane & 7)) << 4));
            float kf[8];
#pragma unroll
            for (int i = 0; i < 4; i++) { kf[2 * i] = bf_lo(k[i]); kf[2 * i + 1] = bf_hi(k[i]); }
#pragma unroll
            for (int h = 0; h < 4; h++) {
                const float4 qa = lds_f4(sb + SM_Q + (ch * 4 + h) * 32), qb = lds_f4(sb + SM_Q + (ch * 4 + h) * 32 + 16);
                sv[h] = fmaf(qa.x, kf[0], sv[h]); sv[h] = fmaf(qa.y, kf[1], sv[h]);
                sv[h] = fmaf(qa.z, kf[2], sv[h]); sv[h] = fmaf(qa.w, kf[3], sv[h]);
                sv[h] = fmaf(qb.x, kf[4], sv[h]); sv[h] = fmaf(qb.y, kf[5], sv[h]);
                sv[h] = fmaf(qb.z, kf[6], sv[h]); sv[h] = fmaf(qb.w, kf[7], sv[h]);
            }
        }
        __syncwarp();
        if (lane == 0) mbar_arrive(bars + (BAR_EK + u) * 8);
        const float scale = 0.08838834764831845f;
        float m[4];
#pragma unroll
        for (int h = 0; h < 4; h++) { sv[h] = bf16r(bf16r(sv[h]) * scale); m[h] = warp_max(sv[h]); }
        if (lane == 0) sts_f4(sb + SM_MAX + u * 16, m[0], m[1], m[2], m[3]);
        TS(5);
        bar_sync(2, NCT);
        {
            const float4 t = lds_f4(sb + SM_MAX + (lane & 7) * 16);
            m[0] = warp_max(t.x); m[1] = warp_max(t.y); m[2] = warp_max(t.z); m[3] = warp_max(t.w);
        }
#pragma unroll
        for (int h = 0; h < 4; h++) sv[h] = ex2((sv[h] - m[h]) * LOG2E);
        sts_f4(sb + SM_P + (u * 32 + lane) * 16, bf16r(sv[0]), bf16r(sv[1]), bf16r(sv[2]), bf16r(sv[3]));
        halve(sv, 4, 16, lane);
        halve(sv, 2, 8, lane);
        float l = sv[0];
        l += __shfl_xor_sync(~0u, l, 4);
        l += __shfl_xor_sync(~0u, l, 2);
        l += __shfl_xor_sync(~0u, l, 1);
        if ((lane & 7) == 0) sts_f1(sb + SM_SUM + (u * 4 + (lane >> 3)) * 4, l);
        bar_sync(4, NCT + 32);
        TS(6);
    }

    unsigned long long w[6][2] = {};
    const unsigned long long* so = &sc->ox[(((fg & 1) * 256 + r * 32 + u) * 4 + ft) * 2];
    const unsigned long long* sa = &sc->ax[(((fg & 1) * 112 + r * 14 + (u < 7 ? u : 0)) * 4 + ft) * 2];
    {
        float acc[8] = {};
        const int kg = lane >> 3, dl = lane & 7;
        const int cidx = (u & 3) * 2 + (dl >> 2);
        const uint32_t voff = (u >> 2) * 4096 + kg * 256 + (dl & 3) * 4;
        const uint32_t sw0 = (cidx ^ (2 * kg)) << 4, sw1 = (cidx ^ (2 * kg + 1)) << 4;
#pragma unroll
        for (int i = 0; i < 8; i++) {
            mbar_wait(bars + (CH_V + i) * 8);
#pragma unroll
            for (int it = 0; it < 8; it++) {
                const uint32_t vw = lds_u1(sb + slot_off(CH_V + i) + voff + (it >> 1) * 1024 + (it & 1) * 128 + ((it & 1) ? sw1 : sw0));
                const float4 pp = lds_f4(sb + SM_P + (i * 32 + (it >> 1) * 8 + (it & 1)) * 16 + kg * 32);
                const float lo = bf_lo(vw), hi = bf_hi(vw);
                acc[0] = fmaf(pp.x, lo, acc[0]); acc[1] = fmaf(pp.x, hi, acc[1]);
                acc[2] = fmaf(pp.y, lo, acc[2]); acc[3] = fmaf(pp.y, hi, acc[3]);
                acc[4] = fmaf(pp.z, lo, acc[4]); acc[5] = fmaf(pp.z, hi, acc[5]);
                acc[6] = fmaf(pp.w, lo, acc[6]); acc[7] = fmaf(pp.w, hi, acc[7]);
            }
            if (i == 0) {
                __syncwarp();
                if (lane == 0) mbar_arrive(bars + BAR_EV * 8);
                asm volatile("barrier.cluster.wait.acquire.aligned;" ::: "memory");
            }
        }
        TS(8);
        halve(acc, 8, 16, lane);
        halve(acc, 4, 8, lane);
        const uint32_t dst = mapa(sb + SM_INB + j * 256 + lane * 8, u);
        const uint32_t rbar = mapa(bars + BAR_PO * 8, u);
        asm volatile("st.async.weak.shared::cluster.mbarrier::complete_tx::bytes.v2.f32 [%0], {%1, %2}, [%3];"
                     ::"r"(dst), "f"(acc[0]), "f"(acc[1]), "r"(rbar) : "memory");
        TS(9);
    }

    {
        unsigned long long v[7][2] = {};
        const unsigned long long* psrc = &sc->px[(g16 * 8 + 1) * 64 + lane * 2];
        if (u == 0 && r == 0) {
#pragma unroll
            for (int i = 0; i < 7; i++) ld_ll2(psrc + i * 64, v[i][0], v[i][1]);
        }
        uint32_t wa[4][2][4];
        const int row = u * 16 + lrow;
        const uint32_t ro0 = row * 64 + ((lchk ^ ((row >> 1) & 3)) << 4), ro1 = row * 64 + (((2 + lchk) ^ ((row >> 1) & 3)) << 4);
        auto poll = [&](int lo, int hi) {
            if (lane < 8) {
                unsigned n = 0;
                while (true) {
#pragma unroll
                    for (int q = 0; q < 6; q++)
                        if (q >= lo && q < hi && !tag_ok(w[q][0], w[q][1], tag))
                            ld_ll2(q < 4 ? so + q * 64 : sa + (q - 4) * 56, w[q][0], w[q][1]);
                    bool ok = true;
#pragma unroll
                    for (int q = 0; q < 6; q++)
                        if (q >= lo && q < hi) ok = ok && tag_ok(w[q][0], w[q][1], tag);
                    if (ok || ++n >= SPIN_LIMIT) break;
                    __nanosleep(20);
                }
            }
            __syncwarp();
        };
        poll(4, 6);
#pragma unroll
        for (int q = 0; q < 4; q++) {
            mbar_wait(bars + (CH_WO + q) * 8);
            ldsm4t(wa[q][0], sb + slot_off(CH_WO + q) + ro0);
            ldsm4t(wa[q][1], sb + slot_off(CH_WO + q) + ro1);
        }
        TS(12);
        poll(0, 4);
        TS(13);
        float acc[2][4] = {}, acc2[2][4] = {};
#pragma unroll
        for (int q = 0; q < 4; q += 2) {
#pragma unroll
            for (int mt = 0; mt < 2; mt++) {
                mma16816(acc[mt], wa[q][mt][0], wa[q][mt][1], wa[q][mt][2], wa[q][mt][3], (uint32_t)w[q][0], (uint32_t)w[q][1]);
                mma16816(acc2[mt], wa[q + 1][mt][0], wa[q + 1][mt][1], wa[q + 1][mt][2], wa[q + 1][mt][3], (uint32_t)w[q + 1][0],
                         (uint32_t)w[q + 1][1]);
            }
        }
        if (u < 7) {
            mbar_wait(bars + CH_W2 * 8);
            gemv_tile64(acc, sb + slot_off(CH_W2), row, lchk, (uint32_t)w[4][0], (uint32_t)w[4][1]);
            mbar_wait(bars + (CH_W2 + 1) * 8);
            gemv_tile64(acc2, sb + slot_off(CH_W2 + 1), row, lchk, (uint32_t)w[5][0], (uint32_t)w[5][1]);
        }
#pragma unroll
        for (int mt = 0; mt < 2; mt++)
#pragma unroll
            for (int i = 0; i < 4; i++) acc[mt][i] += acc2[mt][i];
        TS(14);
        if (ft == 0) {
            const uint32_t rb = sb + SM_REDO + u * 256;
#pragma unroll
            for (int mt = 0; mt < 2; mt++) {
                sts_f1(rb + (mt * 16 + fg) * 4, acc[mt][0]);
                sts_f1(rb + 128 + (mt * 16 + fg) * 4, acc[mt][1]);
                sts_f1(rb + (mt * 16 + fg + 8) * 4, acc[mt][2]);
                sts_f1(rb + 128 + (mt * 16 + fg + 8) * 4, acc[mt][3]);
            }
        }
        if (u != 0) { bar_arrive(2, NCT); return; }
        bar_sync(2, NCT);
        float2 s = make_float2(0.f, 0.f);
#pragma unroll
        for (int k = 0; k < NCW; k++) {
            float2 t = lds_f2(sb + SM_REDO + k * 256 + lane * 8);
            s.x += t.x; s.y += t.y;
        }
        if (r != 0) {
            st_ll2(&sc->px[(g16 * 8 + r) * 64 + lane * 2], __float_as_uint(s.x), __float_as_uint(s.y), tag);
            TS(15);
            return;
        }
        TS(15);
        unsigned n = 0;
        while (true) {
#pragma unroll
            for (int i = 0; i < 7; i++)
                if (!tag_ok(v[i][0], v[i][1], tag)) ld_ll2(psrc + i * 64, v[i][0], v[i][1]);
            bool ok = true;
#pragma unroll
            for (int i = 0; i < 7; i++) ok = ok && tag_ok(v[i][0], v[i][1], tag);
            if (ok || ++n >= SPIN_LIMIT) break;
        }
#pragma unroll
        for (int i = 0; i < 7; i++) { s.x += __uint_as_float((uint32_t)v[i][0]); s.y += __uint_as_float((uint32_t)v[i][1]); }
        reinterpret_cast<uint32_t*>(p.out)[(lane >> 4) * 256 + g16 * 16 + (lane & 15)] =
            pack_bf16(bf_lo(xres) + s.x, bf_hi(xres) + s.y);
        __syncwarp();
        if (c == 0 && lane == 0) sc->epoch = tag;
        TS(16);
    }
}

typedef CUresult (*EncodeTiledFn)(CUtensorMap*, CUtensorMapDataType, cuuint32_t, void*, const cuuint64_t*, const cuuint64_t*,
                                  const cuuint32_t*, const cuuint32_t*, CUtensorMapInterleave, CUtensorMapSwizzle,
                                  CUtensorMapL2promotion, CUtensorMapFloatOOBfill);

void make_map(EncodeTiledFn enc, CUtensorMap* m, const void* base, uint64_t cols, uint64_t rows, uint32_t box_c, uint32_t box_r,
              CUtensorMapSwizzle sw) {
    cuuint64_t gd[2] = {cols, rows};
    cuuint64_t gs[1] = {cols * 2};
    cuuint32_t bd[2] = {box_c, box_r};
    cuuint32_t es[2] = {1, 1};
    enc(m, CU_TENSOR_MAP_DATA_TYPE_BFLOAT16, 2, const_cast<void*>(base), gd, gs, bd, es, CU_TENSOR_MAP_INTERLEAVE_NONE, sw,
        CU_TENSOR_MAP_L2_PROMOTION_L2_128B, CU_TENSOR_MAP_FLOAT_OOB_FILL_NONE);
}

}

extern "C" void kernel_launch(void* const* d_in, const int* in_sizes, int n_in, void* d_out, int out_size) {
    (void)in_sizes; (void)n_in; (void)out_size;
    static EncodeTiledFn enc = nullptr;
    static Scratch* sc = nullptr;
    if (!enc) {
        void* fn = nullptr;
        cudaDriverEntryPointQueryResult st;
        cudaGetDriverEntryPoint("cuTensorMapEncodeTiled", &fn, cudaEnableDefault, &st);
        enc = (EncodeTiledFn)fn;
        cudaFuncSetAttribute(fused_decode_kernel, cudaFuncAttributeMaxDynamicSharedMemorySize, SM_TOTAL);
        void* sp = nullptr;
        cudaGetSymbolAddress(&sp, g_scratch);
        sc = (Scratch*)sp;
    }
    Params p;
    make_map(enc, &p.k, d_in[1], 128, 2 * 8 * SK, 64, 32, CU_TENSOR_MAP_SWIZZLE_128B);
    make_map(enc, &p.v, d_in[2], 128, 2 * 8 * SK, 64, 32, CU_TENSOR_MAP_SWIZZLE_128B);
    make_map(enc, &p.wq, d_in[3], 4096, 512, 32, 128, CU_TENSOR_MAP_SWIZZLE_NONE);
    make_map(enc, &p.wo, d_in[4], 512, 4096, 32, 128, CU_TENSOR_MAP_SWIZZLE_64B);
    make_map(enc, &p.w1, d_in[6], FF, 512, 16, 256, CU_TENSOR_MAP_SWIZZLE_NONE);
    make_map(enc, &p.w2, d_in[8], 512, FF, 32, 112, CU_TENSOR_MAP_SWIZZLE_64B);
    p.x = (const __nv_bfloat16*)d_in[0];
    p.b1 = (const __nv_bfloat16*)d_in[7];
    p.out = (__nv_bfloat16*)d_out;
    p.sc = sc;
    fused_decode_kernel<<<NCTA, NTHREADS, SM_TOTAL, cudaStreamPerThread>>>(p);
}
```

```cpp
#include <cuda_runtime.h>
#include <cuda_bf16.h>
#include <cuda.h>
#include <stdint.h>

namespace {

constexpr int D_MODEL = 512;
constexpr int SK = 8192;
constexpr int WIN = 2048;
constexpr int WIN0 = SK - WIN;
constexpr int FF = 1792;

constexpr int NCTA = 128;
constexpr int NCW = 8;
constexpr int NCT = NCW * 32;
constexpr int NTHREADS = (NCW + 2) * 32;

constexpr int CH_WQ = 0, CH_W1 = 8, CH_K = 10, CH_V = 18, CH_WO = 26, CH_W2 = 30, NCHUNK = 32;
constexpr int NSLOT = 13;
#define WINDOW 8
#define GATE 2
__host__ __device__ constexpr int slot_off(int chunk) { return (chunk % NSLOT) * 8192; }

constexpr int BAR_FULL = 0;
constexpr int BAR_EMPTY = NCHUNK;
constexpr int BAR_Q = BAR_EMPTY + CH_V + 1;
constexpr int BAR_ST = BAR_Q + 1;
constexpr int BAR_PO = BAR_ST + 1;
constexpr int BAR_GATE = BAR_PO + 1;
constexpr int NBAR = BAR_GATE + 1;

constexpr int SM_RING = 0;
constexpr int SM_INB = NSLOT * 8192;
constexpr int SM_INS = SM_INB + 2048;
constexpr int SM_REDA = SM_INB;
constexpr int SM_XN = SM_INS + 256;
constexpr int SM_REDB = SM_XN + 2048;
constexpr int SM_P = SM_XN;
constexpr int SM_Q = SM_XN + 4096;
constexpr int SM_REDO = SM_Q;
constexpr int SM_MAX = SM_Q + 2048;
constexpr int SM_SUM = SM_MAX + 128;
constexpr int SM_BAR = SM_SUM + 128;
constexpr int SM_EPOCH = SM_BAR + NBAR * 8;
constexpr int SM_TOTAL = SM_EPOCH + 16;
static_assert(SM_TOTAL <= 115712, "two CTAs must fit on one SM");

constexpr unsigned SPIN_LIMIT = 1u << 22;

struct Scratch {
    unsigned epoch;
    unsigned pad[31];
    unsigned long long ox[2 * 256 * 8];
    unsigned long long ax[2 * 112 * 8];
    unsigned long long px[16 * 8 * 64];
};

__device__ Scratch g_scratch;

struct Params {
    CUtensorMap wq, k, v, w1, wo, w2;
    const __nv_bfloat16* x;
    const __nv_bfloat16* b1;
    __nv_bfloat16* out;
    Scratch* sc;
};

__device__ __forceinline__ uint32_t smem_u32(const void* p) { return (uint32_t)__cvta_generic_to_shared(p); }
__device__ __forceinline__ void mbar_init(uint32_t bar, uint32_t cnt) {
    asm volatile("mbarrier.init.shared::cta.b64 [%0], %1;" ::"r"(bar), "r"(cnt) : "memory");
}
__device__ __forceinline__ void mbar_expect_tx(uint32_t bar, uint32_t bytes) {
    asm volatile("mbarrier.arrive.expect_tx.shared::cta.b64 _, [%0], %1;" ::"r"(bar), "r"(bytes) : "memory");
}
__device__ __forceinline__ void mbar_arrive(uint32_t bar) {
    asm volatile("mbarrier.arrive.shared::cta.b64 _, [%0];" ::"r"(bar) : "memory");
}
__device__ __forceinline__ void mbar_wait(uint32_t bar) {
    unsigned n = 0;
    uint32_t ok;
    do {
        asm volatile("{\n.reg .pred p;\nmbarrier.try_wait.parity.shared::cta.b64 p, [%1], 0;\nselp.u32 %0, 1, 0, p;\n}"
                     : "=r"(ok) : "r"(bar) : "memory");
    } while (!ok && ++n < SPIN_LIMIT);
}
__device__ __forceinline__ void mbar_wait_cluster(uint32_t bar) {
    unsigned n = 0;
    uint32_t ok;
    do {
        asm volatile("{\n.reg .pred p;\nmbarrier.try_wait.parity.acquire.cluster.shared::cta.b64 p, [%1], 0;\nselp.u32 %0, 1, 0, p;\n}"
                     : "=r"(ok) : "r"(bar) : "memory");
    } while (!ok && ++n < SPIN_LIMIT);
}
__device__ __forceinline__ void tma2d(uint32_t dst, const CUtensorMap* tm, int c0, int c1, uint32_t bar) {
    asm volatile("cp.async.bulk.tensor.2d.shared::cluster.global.mbarrier::complete_tx::bytes [%0], [%1, {%3, %4}], [%2];"
                 ::"r"(dst), "l"((uint64_t)tm), "r"(bar), "r"(c0), "r"(c1) : "memory");
}
__device__ __forceinline__ uint32_t mapa(uint32_t addr, uint32_t rank) {
    uint32_t r;
    asm("mapa.shared::cluster.u32 %0, %1, %2;" : "=r"(r) : "r"(addr), "r"(rank));
    return r;
}
__device__ __forceinline__ void bar_sync(int id, int n) { asm volatile("bar.sync %0, %1;" ::"r"(id), "r"(n) : "memory"); }
__device__ __forceinline__ void bar_arrive(int id, int n) { asm volatile("bar.arrive %0, %1;" ::"r"(id), "r"(n) : "memory"); }

__device__ __forceinline__ void ldsm4(uint32_t (&r)[4], uint32_t addr) {
    asm volatile("ldmatrix.sync.aligned.m8n8.x4.shared.b16 {%0,%1,%2,%3}, [%4];"
                 : "=r"(r[0]), "=r"(r[1]), "=r"(r[2]), "=r"(r[3]) : "r"(addr) : "memory");
}
__device__ __forceinline__ void ldsm4t(uint32_t (&r)[4], uint32_t addr) {
    asm volatile("ldmatrix.sync.aligned.m8n8.x4.trans.shared.b16 {%0,%1,%2,%3}, [%4];"
                 : "=r"(r[0]), "=r"(r[1]), "=r"(r[2]), "=r"(r[3]) : "r"(addr) : "memory");
}
__device__ __forceinline__ void mma16816(float (&c)[4], uint32_t a0, uint32_t a1, uint32_t a2, uint32_t a3, uint32_t b0, uint32_t b1) {
    asm volatile("mma.sync.aligned.m16n8k16.row.col.f32.bf16.bf16.f32 {%0,%1,%2,%3}, {%4,%5,%6,%7}, {%8,%9}, {%0,%1,%2,%3};"
                 : "+f"(c[0]), "+f"(c[1]), "+f"(c[2]), "+f"(c[3])
                 : "r"(a0), "r"(a1), "r"(a2), "r"(a3), "r"(b0), "r"(b1));
}
__device__ __forceinline__ void st_ll1(unsigned long long* p, uint32_t d, uint32_t tag) {
    unsigned long long w = ((unsigned long long)tag << 32) | d;
    asm volatile("st.relaxed.gpu.global.b64 [%0], %1;" ::"l"(p), "l"(w) : "memory");
}
__device__ __forceinline__ void st_ll2(unsigned long long* p, uint32_t d0, uint32_t d1, uint32_t tag) {
    unsigned long long w0 = ((unsigned long long)tag << 32) | d0, w1 = ((unsigned long long)tag << 32) | d1;
    asm volatile("st.relaxed.gpu.global.v2.b64 [%0], {%1, %2};" ::"l"(p), "l"(w0), "l"(w1) : "memory");
}
__device__ __forceinline__ void ld_ll2(const unsigned long long* p, unsigned long long& w0, unsigned long long& w1) {
    asm volatile("ld.relaxed.gpu.global.v2.b64 {%0, %1}, [%2];" : "=l"(w0), "=l"(w1) : "l"(p) : "memory");
}
__device__ __forceinline__ bool tag_ok(unsigned long long w0, unsigned long long w1, uint32_t tag) {
    return (uint32_t)(w0 >> 32) == tag && (uint32_t)(w1 >> 32) == tag;
}
__device__ __forceinline__ float ex2(float x) {
    float y;
    asm("ex2.approx.ftz.f32 %0, %1;" : "=f"(y) : "f"(x));
    return y;
}
__device__ __forceinline__ float bf16r(float x) { return __bfloat162float(__float2bfloat16_rn(x)); }
__device__ __forceinline__ uint32_t pack_bf16(float lo, float hi) {
    __nv_bfloat162 v = __floats2bfloat162_rn(lo, hi);
    return *reinterpret_cast<uint32_t*>(&v);
}
__device__ __forceinline__ float bf_lo(uint32_t u) { return __uint_as_float(u << 16); }
__device__ __forceinline__ float bf_hi(uint32_t u) { return __uint_as_float(u & 0xffff0000u); }
__device__ __forceinline__ float2 lds_f2(uint32_t a) {
    float2 v;
    asm volatile("ld.shared.v2.f32 {%0, %1}, [%2];" : "=f"(v.x), "=f"(v.y) : "r"(a) : "memory");
    return v;
}
__device__ __forceinline__ float lds_f1(uint32_t a) {
    float v;
    asm volatile("ld.shared.f32 %0, [%1];" : "=f"(v) : "r"(a) : "memory");
    return v;
}
__device__ __forceinline__ uint32_t lds_u1(uint32_t a) {
    uint32_t v;
    asm volatile("ld.shared.u32 %0, [%1];" : "=r"(v) : "r"(a) : "memory");
    return v;
}
__device__ __forceinline__ void lds_u4(uint32_t* r, uint32_t a) {
    asm volatile("ld.shared.v4.u32 {%0,%1,%2,%3}, [%4];" : "=r"(r[0]), "=r"(r[1]), "=r"(r[2]), "=r"(r[3]) : "r"(a) : "memory");
}
__device__ __forceinline__ float4 lds_f4(uint32_t a) {
    float4 v;
    asm volatile("ld.shared.v4.f32 {%0,%1,%2,%3}, [%4];" : "=f"(v.x), "=f"(v.y), "=f"(v.z), "=f"(v.w) : "r"(a) : "memory");
    return v;
}
__device__ __forceinline__ void sts_f2(uint32_t a, float x, float y) {
    asm volatile("st.shared.v2.f32 [%0], {%1, %2};" ::"r"(a), "f"(x), "f"(y) : "memory");
}
__device__ __forceinline__ void sts_f4(uint32_t a, float x, float y, float z, float w) {
    asm volatile("st.shared.v4.f32 [%0], {%1,%2,%3,%4};" ::"r"(a), "f"(x), "f"(y), "f"(z), "f"(w) : "memory");
}
template <int N>
__device__ __forceinline__ void halve(float (&v)[N], int n, int mask, int lane) {
    const bool up = lane & mask;
#pragma unroll
    for (int i = 0; i < N / 2; i++)
        if (i < n / 2) {
            const float keep = up ? v[i + n / 2] : v[i], send = up ? v[i] : v[i + n / 2];
            v[i] = keep + __shfl_xor_sync(~0u, send, mask);
        }
}
__device__ __forceinline__ float warp_max(float x) {
    int i = __float_as_int(x);
    i ^= (i >> 31) & 0x7fffffff;
    i = __reduce_max_sync(~0u, i);
    i ^= (i >> 31) & 0x7fffffff;
    return __int_as_float(i);
}
__device__ __forceinline__ void gemv_piece(float (&acc)[16], uint32_t waddr, uint32_t xaddr) {
    uint32_t w[4];
    lds_u4(w, waddr);
    const uint32_t xw = lds_u1(xaddr);
    const float x0 = bf_lo(xw), x1 = bf_hi(xw);
#pragma unroll
    for (int i = 0; i < 4; i++) {
        const float lo = bf_lo(w[i]), hi = bf_hi(w[i]);
        acc[2 * i] = fmaf(x0, lo, acc[2 * i]);
        acc[2 * i + 1] = fmaf(x0, hi, acc[2 * i + 1]);
        acc[8 + 2 * i] = fmaf(x1, lo, acc[8 + 2 * i]);
        acc[8 + 2 * i + 1] = fmaf(x1, hi, acc[8 + 2 * i + 1]);
    }
}
__device__ __forceinline__ void sts_f1(uint32_t a, float v) { asm volatile("st.shared.f32 [%0], %1;" ::"r"(a), "f"(v) : "memory"); }
__device__ __forceinline__ void sts_u1(uint32_t a, uint32_t v) { asm volatile("st.shared.u32 [%0], %1;" ::"r"(a), "r"(v) : "memory"); }
__device__ __forceinline__ void sts_u4(uint32_t a, uint32_t x, uint32_t y, uint32_t z, uint32_t w) {
    asm volatile("st.shared.v4.u32 [%0], {%1,%2,%3,%4};" ::"r"(a), "r"(x), "r"(y), "r"(z), "r"(w) : "memory");
}

#define TS(i) do { } while (0)

__device__ __forceinline__ void gemv_tile64(float (&acc)[2][4], uint32_t base, int row, int lchk, uint32_t b0, uint32_t b1) {
    uint32_t a0[4], a1[4];
    const uint32_t ra = base + row * 64;
    const int sw = (row >> 1) & 3;
    ldsm4t(a0, ra + ((lchk ^ sw) << 4));
    ldsm4t(a1, ra + (((2 + lchk) ^ sw) << 4));
    mma16816(acc[0], a0[0], a0[1], a0[2], a0[3], b0, b1);
    mma16816(acc[1], a1[0], a1[1], a1[2], a1[3], b0, b1);
}

__global__ void __cluster_dims__(8, 1, 1) __launch_bounds__(NTHREADS, 2) fused_decode_kernel(const __grid_constant__ Params p) {
    extern __shared__ __align__(1024) uint8_t smem[];
    const uint32_t sb = smem_u32(smem);
    const uint32_t bars = sb + SM_BAR;
    const int c = blockIdx.x;
    const int warp = threadIdx.x >> 5, lane = threadIdx.x & 31;
    const int bh = c >> 3, j = c & 7;
    const int r = c >> 4, g16 = c & 15;

    if (warp == NCW) {
        const int krow = bh * SK + WIN0 + j * 256;
        if (lane == 0) {
#pragma unroll
            for (int i = 0; i < CH_W1; i++) mbar_init(bars + i * 8, 1);
            asm volatile("fence.proxy.async.shared::cta;" ::: "memory");
#pragma unroll
            for (int i = 0; i < CH_W1; i++) {
                mbar_expect_tx(bars + i * 8, 8192);
                tma2d(sb + slot_off(i), &p.wq, (bh & 7) * 512 + 64 * j, 64 * i, bars + i * 8);
            }
#pragma unroll
            for (int k = CH_W1; k < NCHUNK; k++) mbar_init(bars + k * 8, 1);
            asm volatile("fence.proxy.async.shared::cta;" ::: "memory");
        }
        __syncwarp();
        asm volatile("barrier.cluster.arrive.relaxed.aligned;" ::: "memory");
        bar_sync(1, NTHREADS);
        if (lane == 0) {
#pragma unroll
            for (int i = CH_W1; i < CH_WO; i++) {
                const uint32_t bar = bars + i * 8;
                const uint32_t dst = sb + slot_off(i);
                if (i >= WINDOW) mbar_wait(bar - WINDOW * 8);
                if (i >= NSLOT) mbar_wait(bars + (BAR_EMPTY + i - NSLOT) * 8);
                if (i < CH_K) {
                    const int q = i - CH_W1;
                    if (c < 112) {
                        mbar_expect_tx(bar, 8192);
                        tma2d(dst, &p.w1, 16 * c, 256 * q, bar);
                    } else {
                        mbar_expect_tx(bar, 0);
                    }
                } else if (i < CH_V) {
                    const int q = i - CH_K;
                    mbar_expect_tx(bar, 8192);
                    tma2d(dst, &p.k, 0, krow + q * 32, bar);
                    tma2d(dst + 4096, &p.k, 64, krow + q * 32, bar);
                } else {
                    const int q = i - CH_V;
                    mbar_expect_tx(bar, 8192);
                    tma2d(dst, &p.v, 0, krow + q * 32, bar);
                    tma2d(dst + 4096, &p.v, 64, krow + q * 32, bar);
                }
                TS(i);
            }
            if (GATE >= 0) mbar_wait(bars + (CH_V + GATE) * 8);
        }
        __syncwarp();
        asm volatile("barrier.cluster.wait.acquire.aligned;" ::: "memory");
        if (GATE >= 0 && lane < 8)
            asm volatile("mbarrier.arrive.relaxed.cluster.shared::cluster.b64 _, [%0];" ::"r"(mapa(bars + BAR_GATE * 8, lane)) : "memory");
        if (lane == 0) {
            if (GATE >= 0) mbar_wait(bars + BAR_GATE * 8);
#pragma unroll
            for (int i = CH_WO; i < NCHUNK; i++) {
                const uint32_t bar = bars + i * 8;
                const uint32_t dst = sb + slot_off(i);
                mbar_wait(bar - WINDOW * 8);
                mbar_wait(bars + (BAR_EMPTY + i - NSLOT) * 8);
                if (i < CH_W2) {
                    const int q = i - CH_WO;
                    mbar_expect_tx(bar, 8192);
                    tma2d(dst, &p.wo, 32 * g16, 512 * r + 128 * q, bar);
                } else {
                    const int q = i - CH_W2;
                    mbar_expect_tx(bar, 7168);
                    tma2d(dst, &p.w2, 32 * g16, 224 * r + 112 * q, bar);
                }
                TS(i - 24);
            }
        }
        return;
    }

    Scratch* const sc = p.sc;
    const float LOG2E = 1.4426950408889634f;

    if (warp == NCW + 1) {
        const uint32_t tag = *reinterpret_cast<volatile unsigned*>(&sc->epoch) + 1u;
        if (lane == 0) {
            mbar_init(bars + BAR_Q * 8, 1);
            mbar_init(bars + BAR_ST * 8, 1);
            mbar_init(bars + BAR_PO * 8, 1);
            mbar_init(bars + BAR_GATE * 8, 8);
            asm volatile("fence.mbarrier_init.release.cluster;" ::: "memory");
            mbar_expect_tx(bars + BAR_Q * 8, 2048);
            mbar_expect_tx(bars + BAR_ST * 8, 256);
            mbar_expect_tx(bars + BAR_PO * 8, 2048);
#pragma unroll
            for (int k = 0; k <= CH_V; k++) mbar_init(bars + (BAR_EMPTY + k) * 8, (k >= CH_K && k < CH_V) ? 1 : NCW);
        }
        __syncwarp();
        asm volatile("barrier.cluster.arrive.relaxed.aligned;" ::: "memory");
        if (lane == 0) sts_u1(sb + SM_EPOCH, tag);
        __syncwarp();
        bar_arrive(1, NTHREADS);
        TS(0);
        asm volatile("barrier.cluster.wait.acquire.aligned;" ::: "memory");
        bar_sync(4, NCT + 32);
        {
            float mx = lds_f1(sb + SM_MAX + lane * 4);
            float sm = lds_f1(sb + SM_SUM + lane * 4);
#pragma unroll
            for (int o = 4; o < 32; o <<= 1) { mx = fmaxf(mx, __shfl_xor_sync(~0u, mx, o)); sm += __shfl_xor_sync(~0u, sm, o); }
            const uint32_t dst = mapa(sb + SM_INS + (j * 4 + (lane & 3)) * 8, lane >> 2);
            const uint32_t rbar = mapa(bars + BAR_ST * 8, lane >> 2);
            asm volatile("st.async.weak.shared::cluster.mbarrier::complete_tx::bytes.v2.f32 [%0], {%1, %2}, [%3];"
                         ::"r"(dst), "f"(mx), "f"(sm), "r"(rbar) : "memory");
        }
        TS(2);
        float coef[8];
        {
            mbar_wait_cluster(bars + BAR_ST * 8);
            const float2 st = lds_f2(sb + SM_INS + lane * 8);
            float gm = st.x;
#pragma unroll
            for (int o = 4; o < 32; o <<= 1) gm = fmaxf(gm, __shfl_xor_sync(~0u, gm, o));
            const float wj = ex2((st.x - gm) * LOG2E);
            float gl = wj * st.y;
#pragma unroll
            for (int o = 4; o < 32; o <<= 1) gl += __shfl_xor_sync(~0u, gl, o);
            const float cj = wj / gl;
#pragma unroll
            for (int k = 0; k < 8; k++) coef[k] = __shfl_sync(~0u, cj, k * 4 + (lane >> 3));
        }
        TS(3);
        mbar_wait_cluster(bars + BAR_PO * 8);
        {
            float o0 = 0.f, o1 = 0.f;
#pragma unroll
            for (int k = 0; k < 8; k++) {
                const float2 v = lds_f2(sb + SM_INB + k * 256 + lane * 8);
                o0 = fmaf(coef[k], v.x, o0);
                o1 = fmaf(coef[k], v.y, o1);
            }
            const int head = (bh & 7) * 4 + (lane >> 3);
            st_ll1(&sc->ox[((bh >> 3) * 256 + head * 8 + j) * 8 + (lane & 3) * 2 + ((lane >> 2) & 1)], pack_bf16(o0, o1), tag);
        }
        TS(4);
        return;
    }

    const int u = warp;
    const int fg = lane >> 2, ft = lane & 3;
    asm volatile("barrier.cluster.arrive.relaxed.aligned;" ::: "memory");

    uint32_t xres = 0;
    uint32_t b1pair = 0;
    if (u < 2) {
        const uint4* x4 = reinterpret_cast<const uint4*>(p.x) + u * 64 + lane * 2;
        const uint4 v0 = __ldg(x4), v1 = __ldg(x4 + 1);
        if (u == 0) xres = __ldg(reinterpret_cast<const uint32_t*>(p.x) + (lane >> 4) * 256 + g16 * 16 + (lane & 15));
        if (u == 1 && c < 112) b1pair = __ldg(reinterpret_cast<const uint32_t*>(p.b1) + c * 8 + (lane & 7));
        const uint32_t a[8] = {v0.x, v0.y, v0.z, v0.w, v1.x, v1.y, v1.z, v1.w};
        float s0 = 0.f;
#pragma unroll
        for (int i = 0; i < 8; i++) s0 += bf_lo(a[i]) + bf_hi(a[i]);
#pragma unroll
        for (int o = 16; o > 0; o >>= 1) s0 += __shfl_xor_sync(~0u, s0, o);
        const float m0 = s0 * (1.f / D_MODEL);
        float q0 = 0.f;
#pragma unroll
        for (int i = 0; i < 8; i++) {
            float d;
            d = bf_lo(a[i]) - m0; q0 += d * d; d = bf_hi(a[i]) - m0; q0 += d * d;
        }
#pragma unroll
        for (int o = 16; o > 0; o >>= 1) q0 += __shfl_xor_sync(~0u, q0, o);
        const float mean = bf16r(m0);
        const float var = bf16r(q0 * (1.f / D_MODEL));
        const float den = bf16r(sqrtf(bf16r(var + 1e-5f)));
        const float rden = 1.f / den;
        uint32_t o[8];
#pragma unroll
        for (int i = 0; i < 8; i++) o[i] = pack_bf16(bf16r(bf_lo(a[i]) - mean) * rden, bf16r(bf_hi(a[i]) - mean) * rden);
        const uint32_t dst = sb + SM_XN + lane * 64 + u * 2;
#pragma unroll
        for (int i = 0; i < 8; i++) {
            asm volatile("st.shared.u16 [%0], %1;" ::"r"(dst + i * 8), "h"((unsigned short)(o[i] & 0xffffu)) : "memory");
            asm volatile("st.shared.u16 [%0], %1;" ::"r"(dst + i * 8 + 4), "h"((unsigned short)(o[i] >> 16)) : "memory");
        }
        TS(0);
    }

    const int lrow = (lane & 7) + ((lane >> 4) << 3);
    const int lchk = (lane >> 3) & 1;

    bar_sync(1, NTHREADS);
    const uint32_t tag = lds_u1(sb + SM_EPOCH);

    {
        float acc[8] = {};
        const int xsh = (bh >> 3) ? 0 : 16;
#pragma unroll
        for (int q = 0; q < 8; q++) {
            mbar_wait(bars + (CH_WQ + q) * 8);
#pragma unroll
            for (int it = 0; it < 2; it++) {
                const int row = u * 8 + it * 4 + (lane >> 3);
                uint32_t w[4];
                lds_u4(w, sb + slot_off(CH_WQ + q) + row * 128 + (lane & 7) * 16);
                const float x = __uint_as_float((lds_u1(sb + SM_XN + (q * 64 + row) * 4) << xsh) & 0xffff0000u);
#pragma unroll
                for (int i = 0; i < 4; i++) {
                    acc[2 * i] = fmaf(x, bf_lo(w[i]), acc[2 * i]);
                    acc[2 * i + 1] = fmaf(x, bf_hi(w[i]), acc[2 * i + 1]);
                }
            }
            __syncwarp();
            if (lane == 0) mbar_arrive(bars + (BAR_EMPTY + CH_WQ + q) * 8);
        }
        TS(1);
        halve(acc, 8, 16, lane);
        halve(acc, 4, 8, lane);
        sts_f2(sb + SM_REDA + u * 256 + ((lane & 7) * 8 + (lane >> 4) * 4 + ((lane >> 3) & 1) * 2) * 4, acc[0], acc[1]);
    }
    asm volatile("barrier.cluster.wait.acquire.aligned;" ::: "memory");
    bar_sync(2, NCT);
    if (u == 0) {
        float2 s = make_float2(0.f, 0.f);
#pragma unroll
        for (int w = 0; w < NCW; w++) {
            float2 v = lds_f2(sb + SM_REDA + w * 256 + lane * 8);
            s.x += v.x; s.y += v.y;
        }
        s.x = bf16r(s.x); s.y = bf16r(s.y);
#pragma unroll
        for (int k = 0; k < 8; k++)
            asm volatile("st.async.weak.shared::cluster.mbarrier::complete_tx::bytes.v2.f32 [%0], {%1, %2}, [%3];"
                         ::"r"(mapa(sb + SM_Q + j * 256 + lane * 8, k)), "f"(s.x), "f"(s.y), "r"(mapa(bars + BAR_Q * 8, k)) : "memory");
        TS(2);
    }

    if (c < 112) {
        float acc[16] = {};
#pragma unroll
        for (int q = 0; q < 2; q++) {
            mbar_wait(bars + (CH_W1 + q) * 8);
#pragma unroll
            for (int it = 0; it < 2; it++) {
                const int row = u * 32 + it * 16 + (lane >> 1);
                gemv_piece(acc, sb + slot_off(CH_W1 + q) + row * 32 + (lane & 1) * 16, sb + SM_XN + (q * 256 + row) * 4);
            }
            __syncwarp();
            if (lane == 0) mbar_arrive(bars + (BAR_EMPTY + CH_W1 + q) * 8);
        }
        TS(10);
        halve(acc, 16, 16, lane);
        halve(acc, 8, 8, lane);
        halve(acc, 4, 4, lane);
        halve(acc, 2, 2, lane);
        sts_f1(sb + SM_REDB + u * 128 + ((lane >> 4) * 16 + (lane & 1) * 8 + ((lane >> 1) & 7)) * 4, acc[0]);
        bar_sync(2, NCT);
        if (u == 1 && lane < 16) {
            float2 s = make_float2(0.f, 0.f);
#pragma unroll
            for (int k = 0; k < NCW; k++) {
                float2 v = lds_f2(sb + SM_REDB + k * 128 + lane * 8);
                s.x += v.x; s.y += v.y;
            }
            float h[2] = {bf16r(bf16r(s.x) + bf_lo(b1pair)), bf16r(bf16r(s.y) + bf_hi(b1pair))};
            float a[2];
#pragma unroll
            for (int i = 0; i < 2; i++) {
                const float e = bf16r(__expf(-fabsf(h[i])));
                const float sp = bf16r(bf16r(log1pf(e)) + fmaxf(h[i], 0.f));
                a[i] = h[i] * bf16r(tanhf(sp));
            }
            const int dp = lane & 7;
            st_ll1(&sc->ax[(((lane >> 3) * 112 + c) * 4 + (dp & 3)) * 2 + (dp >> 2)], pack_bf16(a[0], a[1]), tag);
            TS(11);
        }
    } else if (lane == 0) {
        mbar_arrive(bars + (BAR_EMPTY + CH_W1) * 8);
        mbar_arrive(bars + (BAR_EMPTY + CH_W1 + 1) * 8);
    }
    __syncwarp();

    {
        mbar_wait_cluster(bars + BAR_Q * 8);
        TS(3);
        const int li = lane & 15, hw = lane >> 4;
        float qf[4][8];
#pragma unroll
        for (int h = 0; h < 4; h++) {
            const float4 qa = lds_f4(sb + SM_Q + (h * 128 + li * 8) * 4), qb = lds_f4(sb + SM_Q + (h * 128 + li * 8) * 4 + 16);
            qf[h][0] = qa.x; qf[h][1] = qa.y; qf[h][2] = qa.z; qf[h][3] = qa.w;
            qf[h][4] = qb.x; qf[h][5] = qb.y; qf[h][6] = qb.z; qf[h][7] = qb.w;
        }
        mbar_wait(bars + (CH_K + u) * 8);
        TS(4);
        float sv[4];
        const uint32_t kb = sb + ((CH_K + u) % NSLOT) * 8192 + (li >> 3) * 4096 + hw * 128;
#pragma unroll
        for (int g = 0; g < 4; g++) {
            float acc[16];
#pragma unroll
            for (int kk = 0; kk < 4; kk++) {
                uint32_t k[4];
                lds_u4(k, kb + (g * 8 + kk * 2) * 128 + (((li & 7) ^ (kk * 2 + hw)) << 4));
                float kf[8];
#pragma unroll
                for (int i = 0; i < 4; i++) { kf[2 * i] = bf_lo(k[i]); kf[2 * i + 1] = bf_hi(k[i]); }
#pragma unroll
                for (int h = 0; h < 4; h++) {
                    float a = qf[h][0] * kf[0];
#pragma unroll
                    for (int i = 1; i < 8; i++) a = fmaf(qf[h][i], kf[i], a);
                    acc[kk * 4 + h] = a;
                }
            }
            halve(acc, 16, 8, lane);
            halve(acc, 8, 4, lane);
            halve(acc, 4, 2, lane);
            halve(acc, 2, 1, lane);
            sv[g] = acc[0];
        }
        if (lane == 0) mbar_arrive(bars + (BAR_EMPTY + CH_K + u) * 8);
        const float scale = 0.08838834764831845f;
#pragma unroll
        for (int g = 0; g < 4; g++) sv[g] = bf16r(bf16r(sv[g]) * scale);
        float m = fmaxf(fmaxf(sv[0], sv[1]), fmaxf(sv[2], sv[3]));
#pragma unroll
        for (int o = 4; o < 32; o <<= 1) m = fmaxf(m, __shfl_xor_sync(~0u, m, o));
        if (lane < 4) sts_f1(sb + SM_MAX + (u * 4 + lane) * 4, m);
        TS(5);
        bar_sync(2, NCT);
        m = lds_f1(sb + SM_MAX + lane * 4);
#pragma unroll
        for (int o = 4; o < 32; o <<= 1) m = fmaxf(m, __shfl_xor_sync(~0u, m, o));
        const uint32_t pdst = sb + SM_P + (u * 32 + (li >> 2) * 2 + hw) * 16 + (li & 3) * 4;
#pragma unroll
        for (int g = 0; g < 4; g++) {
            sv[g] = ex2((sv[g] - m) * LOG2E);
            sts_f1(pdst + g * 128, bf16r(sv[g]));
        }
        float l = (sv[0] + sv[1]) + (sv[2] + sv[3]);
#pragma unroll
        for (int o = 4; o < 32; o <<= 1) l += __shfl_xor_sync(~0u, l, o);
        if (lane < 4) sts_f1(sb + SM_SUM + (u * 4 + lane) * 4, l);
        bar_sync(4, NCT + 32);
        TS(6);
    }

    unsigned long long w[6][2] = {};
    const unsigned long long* so = &sc->ox[(((fg & 1) * 256 + r * 32 + u) * 4 + ft) * 2];
    const unsigned long long* sa = &sc->ax[(((fg & 1) * 112 + r * 14 + (u < 7 ? u : 0)) * 4 + ft) * 2];
    {
        float acc[16] = {};
        const int row = ((fg & 3) << 1) | (fg >> 2);
        const uint32_t voff = (u >> 2) * 4096 + row * 128 + ((((u & 3) * 2 + (ft >> 1)) ^ row) << 4) + (ft & 1) * 8;
#pragma unroll
        for (int i = 0; i < 8; i++) {
            mbar_wait(bars + (CH_V + i) * 8);
#pragma unroll
            for (int it = 0; it < 4; it++) {
                uint32_t v0, v1;
                asm volatile("ld.shared.v2.u32 {%0, %1}, [%2];" : "=r"(v0), "=r"(v1) : "r"(sb + slot_off(CH_V + i) + voff + it * 1024) : "memory");
                const float4 pp = lds_f4(sb + SM_P + (i * 32 + it * 8 + row) * 16);
                const float vf[4] = {bf_lo(v0), bf_hi(v0), bf_lo(v1), bf_hi(v1)};
#pragma unroll
                for (int d = 0; d < 4; d++) {
                    acc[d] = fmaf(pp.x, vf[d], acc[d]);
                    acc[4 + d] = fmaf(pp.y, vf[d], acc[4 + d]);
                    acc[8 + d] = fmaf(pp.z, vf[d], acc[8 + d]);
                    acc[12 + d] = fmaf(pp.w, vf[d], acc[12 + d]);
                }
            }
            if (i == 0) {
                __syncwarp();
                if (lane == 0) mbar_arrive(bars + (BAR_EMPTY + CH_V) * 8);
            }
        }
        TS(8);
        halve(acc, 16, 16, lane);
        halve(acc, 8, 8, lane);
        halve(acc, 4, 4, lane);
        const uint32_t dst = mapa(sb + SM_INB + j * 256 + ((lane >> 3) * 8 + ft * 2 + (fg & 1)) * 8, u);
        const uint32_t rbar = mapa(bars + BAR_PO * 8, u);
        asm volatile("st.async.weak.shared::cluster.mbarrier::complete_tx::bytes.v2.f32 [%0], {%1, %2}, [%3];"
                     ::"r"(dst), "f"(acc[0]), "f"(acc[1]), "r"(rbar) : "memory");
        TS(9);
    }

    {
        unsigned long long v[7][2] = {};
        const unsigned long long* psrc = &sc->px[(g16 * 8 + 1) * 64 + lane * 2];
        if (u == 0 && r == 0) {
#pragma unroll
            for (int i = 0; i < 7; i++) ld_ll2(psrc + i * 64, v[i][0], v[i][1]);
        }
        uint32_t wa[4][2][4];
        const int row = u * 16 + lrow;
        const uint32_t ro0 = row * 64 + ((lchk ^ ((row >> 1) & 3)) << 4), ro1 = row * 64 + (((2 + lchk) ^ ((row >> 1) & 3)) << 4);
        auto poll = [&](int lo, int hi) {
            if (lane < 8) {
                unsigned n = 0;
                while (true) {
#pragma unroll
                    for (int q = 0; q < 6; q++)
                        if (q >= lo && q < hi && !tag_ok(w[q][0], w[q][1], tag))
                            ld_ll2(q < 4 ? so + q * 64 : sa + (q - 4) * 56, w[q][0], w[q][1]);
                    bool ok = true;
#pragma unroll
                    for (int q = 0; q < 6; q++)
                        if (q >= lo && q < hi) ok = ok && tag_ok(w[q][0], w[q][1], tag);
                    if (ok || ++n >= SPIN_LIMIT) break;
                    __nanosleep(20);
                }
            }
            __syncwarp();
        };
        poll(4, 6);
#pragma unroll
        for (int q = 0; q < 4; q++) {
            mbar_wait(bars + (CH_WO + q) * 8);
            ldsm4t(wa[q][0], sb + slot_off(CH_WO + q) + ro0);
            ldsm4t(wa[q][1], sb + slot_off(CH_WO + q) + ro1);
        }
        TS(12);
        poll(0, 4);
        TS(13);
        float acc[2][4] = {}, acc2[2][4] = {};
#pragma unroll
        for (int q = 0; q < 4; q += 2) {
#pragma unroll
            for (int mt = 0; mt < 2; mt++) {
                mma16816(acc[mt], wa[q][mt][0], wa[q][mt][1], wa[q][mt][2], wa[q][mt][3], (uint32_t)w[q][0], (uint32_t)w[q][1]);
                mma16816(acc2[mt], wa[q + 1][mt][0], wa[q + 1][mt][1], wa[q + 1][mt][2], wa[q + 1][mt][3], (uint32_t)w[q + 1][0],
                         (uint32_t)w[q + 1][1]);
            }
        }
        if (u < 7) {
            mbar_wait(bars + CH_W2 * 8);
            gemv_tile64(acc, sb + slot_off(CH_W2), row, lchk, (uint32_t)w[4][0], (uint32_t)w[4][1]);
            mbar_wait(bars + (CH_W2 + 1) * 8);
            gemv_tile64(acc2, sb + slot_off(CH_W2 + 1), row, lchk, (uint32_t)w[5][0], (uint32_t)w[5][1]);
        }
#pragma unroll
        for (int mt = 0; mt < 2; mt++)
#pragma unroll
            for (int i = 0; i < 4; i++) acc[mt][i] += acc2[mt][i];
        TS(14);
        if (ft == 0) {
            const uint32_t rb = sb + SM_REDO + u * 256;
#pragma unroll
            for (int mt = 0; mt < 2; mt++) {
                sts_f1(rb + (mt * 16 + fg) * 4, acc[mt][0]);
                sts_f1(rb + 128 + (mt * 16 + fg) * 4, acc[mt][1]);
                sts_f1(rb + (mt * 16 + fg + 8) * 4, acc[mt][2]);
                sts_f1(rb + 128 + (mt * 16 + fg + 8) * 4, acc[mt][3]);
            }
        }
        if (u != 0) { bar_arrive(2, NCT); return; }
        bar_sync(2, NCT);
        float2 s = make_float2(0.f, 0.f);
#pragma unroll
        for (int k = 0; k < NCW; k++) {
            float2 t = lds_f2(sb + SM_REDO + k * 256 + lane * 8);
            s.x += t.x; s.y += t.y;
        }
        if (r != 0) {
            st_ll2(&sc->px[(g16 * 8 + r) * 64 + lane * 2], __float_as_uint(s.x), __float_as_uint(s.y), tag);
            TS(15);
            return;
        }
        TS(15);
        unsigned n = 0;
        while (true) {
#pragma unroll
            for (int i = 0; i < 7; i++)
                if (!tag_ok(v[i][0], v[i][1], tag)) ld_ll2(psrc + i * 64, v[i][0], v[i][1]);
            bool ok = true;
#pragma unroll
            for (int i = 0; i < 7; i++) ok = ok && tag_ok(v[i][0], v[i][1], tag);
            if (ok || ++n >= SPIN_LIMIT) break;
        }
#pragma unroll
        for (int i = 0; i < 7; i++) { s.x += __uint_as_float((uint32_t)v[i][0]); s.y += __uint_as_float((uint32_t)v[i][1]); }
        reinterpret_cast<uint32_t*>(p.out)[(lane >> 4) * 256 + g16 * 16 + (lane & 15)] =
            pack_bf16(bf_lo(xres) + s.x, bf_hi(xres) + s.y);
        __syncwarp();
        if (c == 0 && lane == 0) sc->epoch = tag;
        TS(16);
    }
}

typedef CUresult (*EncodeTiledFn)(CUtensorMap*, CUtensorMapDataType, cuuint32_t, void*, const cuuint64_t*, const cuuint64_t*,
                                  const cuuint32_t*, const cuuint32_t*, CUtensorMapInterleave, CUtensorMapSwizzle,
                                  CUtensorMapL2promotion, CUtensorMapFloatOOBfill);

void make_map(EncodeTiledFn enc, CUtensorMap* m, const void* base, uint64_t cols, uint64_t rows, uint32_t box_c, uint32_t box_r,
              CUtensorMapSwizzle sw) {
    cuuint64_t gd[2] = {cols, rows};
    cuuint64_t gs[1] = {cols * 2};
    cuuint32_t bd[2] = {box_c, box_r};
    cuuint32_t es[2] = {1, 1};
    enc(m, CU_TENSOR_MAP_DATA_TYPE_BFLOAT16, 2, const_cast<void*>(base), gd, gs, bd, es, CU_TENSOR_MAP_INTERLEAVE_NONE, sw,
        CU_TENSOR_MAP_L2_PROMOTION_L2_128B, CU_TENSOR_MAP_FLOAT_OOB_FILL_NONE);
}

}

extern "C" void kernel_launch(void* const* d_in, const int* in_sizes, int n_in, void* d_out, int out_size) {
    (void)in_sizes; (void)n_in; (void)out_size;
    static EncodeTiledFn enc = nullptr;
    static Scratch* sc = nullptr;
    if (!enc) {
        void* fn = nullptr;
        cudaDriverEntryPointQueryResult st;
        cudaGetDriverEntryPoint("cuTensorMapEncodeTiled", &fn, cudaEnableDefault, &st);
        enc = (EncodeTiledFn)fn;
        cudaFuncSetAttribute(fused_decode_kernel, cudaFuncAttributeMaxDynamicSharedMemorySize, SM_TOTAL);
        void* sp = nullptr;
        cudaGetSymbolAddress(&sp, g_scratch);
        sc = (Scratch*)sp;
    }
    Params p;
    make_map(enc, &p.k, d_in[1], 128, 2 * 8 * SK, 64, 32, CU_TENSOR_MAP_SWIZZLE_128B);
    make_map(enc, &p.v, d_in[2], 128, 2 * 8 * SK, 64, 32, CU_TENSOR_MAP_SWIZZLE_128B);
    make_map(enc, &p.wq, d_in[3], 4096, 512, 64, 64, CU_TENSOR_MAP_SWIZZLE_NONE);
    make_map(enc, &p.wo, d_in[4], 512, 4096, 32, 128, CU_TENSOR_MAP_SWIZZLE_64B);
    make_map(enc, &p.w1, d_in[6], FF, 512, 16, 256, CU_TENSOR_MAP_SWIZZLE_NONE);
    make_map(enc, &p.w2, d_in[8], 512, FF, 32, 112, CU_TENSOR_MAP_SWIZZLE_64B);
    p.x = (const __nv_bfloat16*)d_in[0];
    p.b1 = (const __nv_bfloat16*)d_in[7];
    p.out = (__nv_bfloat16*)d_out;
    p.sc = sc;
    fused_decode_kernel<<<NCTA, NTHREADS, SM_TOTAL, cudaStreamPerThread>>>(p);
}
```

```cpp
#include <cuda_runtime.h>
#include <cuda_bf16.h>
#include <cuda.h>
#include <stdint.h>

namespace {

constexpr int D_MODEL = 512;
constexpr int SK = 8192;
constexpr int WIN = 2048;
constexpr int WIN0 = SK - WIN;
constexpr int FF = 1792;

constexpr int NCTA = 128;
constexpr int NCW = 8;
constexpr int NCT = NCW * 32;
constexpr int NTHREADS = (NCW + 2) * 32;

constexpr int CH_WQ = 0, CH_W1 = 8, CH_K = 10, CH_V = 18, CH_WO = 26, CH_W2 = 30, NCHUNK = 32;
constexpr int NSLOT = 13;
#define WINDOW 8
#define GATE 2
__host__ __device__ constexpr int slot_off(int chunk) { return (chunk % NSLOT) * 8192; }

constexpr int BAR_FULL = 0;
constexpr int BAR_EMPTY = NCHUNK;
constexpr int BAR_Q = BAR_EMPTY + CH_V + 1;
constexpr int BAR_ST = BAR_Q + 1;
constexpr int BAR_PO = BAR_ST + 1;
constexpr int BAR_GATE = BAR_PO + 1;
constexpr int NBAR = BAR_GATE + 1;

constexpr int SM_RING = 0;
constexpr int SM_INB = NSLOT * 8192;
constexpr int SM_INS = SM_INB + 2048;
constexpr int SM_REDA = SM_INS + 256;
constexpr int SM_REDB = SM_REDA + 2048;
constexpr int SM_XN = SM_REDB + 1024;
constexpr int SM_P = SM_XN;
constexpr int SM_Q = SM_XN + 2048;
constexpr int SM_REDO = SM_REDA;
constexpr int SM_MAX = SM_Q + 1024;
constexpr int SM_SUM = SM_MAX + 128;
constexpr int SM_BAR = SM_SUM + 128;
constexpr int SM_EPOCH = SM_BAR + NBAR * 8;
constexpr int SM_TOTAL = SM_EPOCH + 16;
static_assert(SM_TOTAL <= 115712, "two CTAs must fit on one SM");

constexpr unsigned SPIN_LIMIT = 1u << 22;

struct Scratch {
    unsigned epoch;
    unsigned pad[31];
    unsigned long long ox[2 * 256 * 8];
    unsigned long long ax[2 * 112 * 8];
    unsigned long long px[16 * 8 * 64];
};

__device__ Scratch g_scratch;

struct Params {
    CUtensorMap wq, k, v, w1, wo, w2;
    const __nv_bfloat16* x;
    const __nv_bfloat16* b1;
    __nv_bfloat16* out;
    Scratch* sc;
};

__device__ __forceinline__ uint32_t smem_u32(const void* p) { return (uint32_t)__cvta_generic_to_shared(p); }
__device__ __forceinline__ void mbar_init(uint32_t bar, uint32_t cnt) {
    asm volatile("mbarrier.init.shared::cta.b64 [%0], %1;" ::"r"(bar), "r"(cnt) : "memory");
}
__device__ __forceinline__ void mbar_expect_tx(uint32_t bar, uint32_t bytes) {
    asm volatile("mbarrier.arrive.expect_tx.shared::cta.b64 _, [%0], %1;" ::"r"(bar), "r"(bytes) : "memory");
}
__device__ __forceinline__ void mbar_arrive(uint32_t bar) {
    asm volatile("mbarrier.arrive.shared::cta.b64 _, [%0];" ::"r"(bar) : "memory");
}
__device__ __forceinline__ void mbar_wait(uint32_t bar) {
    unsigned n = 0;
    uint32_t ok;
    do {
        asm volatile("{\n.reg .pred p;\nmbarrier.try_wait.parity.shared::cta.b64 p, [%1], 0;\nselp.u32 %0, 1, 0, p;\n}"
                     : "=r"(ok) : "r"(bar) : "memory");
    } while (!ok && ++n < SPIN_LIMIT);
}
__device__ __forceinline__ void mbar_wait_cluster(uint32_t bar) {
    unsigned n = 0;
    uint32_t ok;
    do {
        asm volatile("{\n.reg .pred p;\nmbarrier.try_wait.parity.acquire.cluster.shared::cta.b64 p, [%1], 0;\nselp.u32 %0, 1, 0, p;\n}"
                     : "=r"(ok) : "r"(bar) : "memory");
    } while (!ok && ++n < SPIN_LIMIT);
}
__device__ __forceinline__ void tma2d(uint32_t dst, const CUtensorMap* tm, int c0, int c1, uint32_t bar) {
    asm volatile("cp.async.bulk.tensor.2d.shared::cluster.global.mbarrier::complete_tx::bytes [%0], [%1, {%3, %4}], [%2];"
                 ::"r"(dst), "l"((uint64_t)tm), "r"(bar), "r"(c0), "r"(c1) : "memory");
}
__device__ __forceinline__ uint32_t mapa(uint32_t addr, uint32_t rank) {
    uint32_t r;
    asm("mapa.shared::cluster.u32 %0, %1, %2;" : "=r"(r) : "r"(addr), "r"(rank));
    return r;
}
__device__ __forceinline__ void bar_sync(int id, int n) { asm volatile("bar.sync %0, %1;" ::"r"(id), "r"(n) : "memory"); }
__device__ __forceinline__ void bar_arrive(int id, int n) { asm volatile("bar.arrive %0, %1;" ::"r"(id), "r"(n) : "memory"); }

__device__ __forceinline__ void ldsm4(uint32_t (&r)[4], uint32_t addr) {
    asm volatile("ldmatrix.sync.aligned.m8n8.x4.shared.b16 {%0,%1,%2,%3}, [%4];"
                 : "=r"(r[0]), "=r"(r[1]), "=r"(r[2]), "=r"(r[3]) : "r"(addr) : "memory");
}
__device__ __forceinline__ void ldsm4t(uint32_t (&r)[4], uint32_t addr) {
    asm volatile("ldmatrix.sync.aligned.m8n8.x4.trans.shared.b16 {%0,%1,%2,%3}, [%4];"
                 : "=r"(r[0]), "=r"(r[1]), "=r"(r[2]), "=r"(r[3]) : "r"(addr) : "memory");
}
__device__ __forceinline__ void mma16816(float (&c)[4], uint32_t a0, uint32_t a1, uint32_t a2, uint32_t a3, uint32_t b0, uint32_t b1) {
    asm volatile("mma.sync.aligned.m16n8k16.row.col.f32.bf16.bf16.f32 {%0,%1,%2,%3}, {%4,%5,%6,%7}, {%8,%9}, {%0,%1,%2,%3};"
                 : "+f"(c[0]), "+f"(c[1]), "+f"(c[2]), "+f"(c[3])
                 : "r"(a0), "r"(a1), "r"(a2), "r"(a3), "r"(b0), "r"(b1));
}
__device__ __forceinline__ void st_ll1(unsigned long long* p, uint32_t d, uint32_t tag) {
    unsigned long long w = ((unsigned long long)tag << 32) | d;
    asm volatile("st.relaxed.gpu.global.b64 [%0], %1;" ::"l"(p), "l"(w) : "memory");
}
__device__ __forceinline__ void st_ll2(unsigned long long* p, uint32_t d0, uint32_t d1, uint32_t tag) {
    unsigned long long w0 = ((unsigned long long)tag << 32) | d0, w1 = ((unsigned long long)tag << 32) | d1;
    asm volatile("st.relaxed.gpu.global.v2.b64 [%0], {%1, %2};" ::"l"(p), "l"(w0), "l"(w1) : "memory");
}
__device__ __forceinline__ void ld_ll2(const unsigned long long* p, unsigned long long& w0, unsigned long long& w1) {
    asm volatile("ld.relaxed.gpu.global.v2.b64 {%0, %1}, [%2];" : "=l"(w0), "=l"(w1) : "l"(p) : "memory");
}
__device__ __forceinline__ bool tag_ok(unsigned long long w0, unsigned long long w1, uint32_t tag) {
    return (uint32_t)(w0 >> 32) == tag && (uint32_t)(w1 >> 32) == tag;
}
__device__ __forceinline__ float ex2(float x) {
    float y;
    asm("ex2.approx.ftz.f32 %0, %1;" : "=f"(y) : "f"(x));
    return y;
}
__device__ __forceinline__ float bf16r(float x) { return __bfloat162float(__float2bfloat16_rn(x)); }
__device__ __forceinline__ uint32_t pack_bf16(float lo, float hi) {
    __nv_bfloat162 v = __floats2bfloat162_rn(lo, hi);
    return *reinterpret_cast<uint32_t*>(&v);
}
__device__ __forceinline__ float bf_lo(uint32_t u) { return __uint_as_float(u << 16); }
__device__ __forceinline__ float bf_hi(uint32_t u) { return __uint_as_float(u & 0xffff0000u); }
__device__ __forceinline__ float2 lds_f2(uint32_t a) {
    float2 v;
    asm volatile("ld.shared.v2.f32 {%0, %1}, [%2];" : "=f"(v.x), "=f"(v.y) : "r"(a) : "memory");
    return v;
}
__device__ __forceinline__ float lds_f1(uint32_t a) {
    float v;
    asm volatile("ld.shared.f32 %0, [%1];" : "=f"(v) : "r"(a) : "memory");
    return v;
}
__device__ __forceinline__ uint32_t lds_u1(uint32_t a) {
    uint32_t v;
    asm volatile("ld.shared.u32 %0, [%1];" : "=r"(v) : "r"(a) : "memory");
    return v;
}
__device__ __forceinline__ void lds_u4(uint32_t* r, uint32_t a) {
    asm volatile("ld.shared.v4.u32 {%0,%1,%2,%3}, [%4];" : "=r"(r[0]), "=r"(r[1]), "=r"(r[2]), "=r"(r[3]) : "r"(a) : "memory");
}
__device__ __forceinline__ float4 lds_f4(uint32_t a) {
    float4 v;
    asm volatile("ld.shared.v4.f32 {%0,%1,%2,%3}, [%4];" : "=f"(v.x), "=f"(v.y), "=f"(v.z), "=f"(v.w) : "r"(a) : "memory");
    return v;
}
__device__ __forceinline__ void sts_f2(uint32_t a, float x, float y) {
    asm volatile("st.shared.v2.f32 [%0], {%1, %2};" ::"r"(a), "f"(x), "f"(y) : "memory");
}
__device__ __forceinline__ void sts_f4(uint32_t a, float x, float y, float z, float w) {
    asm volatile("st.shared.v4.f32 [%0], {%1,%2,%3,%4};" ::"r"(a), "f"(x), "f"(y), "f"(z), "f"(w) : "memory");
}
__device__ __forceinline__ void sts_f1(uint32_t a, float v) { asm volatile("st.shared.f32 [%0], %1;" ::"r"(a), "f"(v) : "memory"); }
__device__ __forceinline__ void sts_u1(uint32_t a, uint32_t v) { asm volatile("st.shared.u32 [%0], %1;" ::"r"(a), "r"(v) : "memory"); }
__device__ __forceinline__ void sts_u4(uint32_t a, uint32_t x, uint32_t y, uint32_t z, uint32_t w) {
    asm volatile("st.shared.v4.u32 [%0], {%1,%2,%3,%4};" ::"r"(a), "r"(x), "r"(y), "r"(z), "r"(w) : "memory");
}

#define TS(i) do { } while (0)

__device__ __forceinline__ void gemv_tile64(float (&acc)[2][4], uint32_t base, int row, int lchk, uint32_t b0, uint32_t b1) {
    uint32_t a0[4], a1[4];
    const uint32_t ra = base + row * 64;
    const int sw = (row >> 1) & 3;
    ldsm4t(a0, ra + ((lchk ^ sw) << 4));
    ldsm4t(a1, ra + (((2 + lchk) ^ sw) << 4));
    mma16816(acc[0], a0[0], a0[1], a0[2], a0[3], b0, b1);
    mma16816(acc[1], a1[0], a1[1], a1[2], a1[3], b0, b1);
}

__global__ void __cluster_dims__(8, 1, 1) __launch_bounds__(NTHREADS, 2) fused_decode_kernel(const __grid_constant__ Params p) {
    extern __shared__ __align__(1024) uint8_t smem[];
    const uint32_t sb = smem_u32(smem);
    const uint32_t bars = sb + SM_BAR;
    const int c = blockIdx.x;
    const int warp = threadIdx.x >> 5, lane = threadIdx.x & 31;
    const int bh = c >> 3, j = c & 7;
    const int r = c >> 4, g16 = c & 15;

    if (warp == NCW) {
        const int krow = bh * SK + WIN0 + j * 256;
        if (lane == 0) {
#pragma unroll
            for (int i = 0; i < CH_W1; i++) mbar_init(bars + i * 8, 1);
            asm volatile("fence.proxy.async.shared::cta;" ::: "memory");
#pragma unroll
            for (int i = 0; i < CH_W1; i++) {
                mbar_expect_tx(bars + i * 8, 8192);
                tma2d(sb + slot_off(i), &p.wq, (bh & 7) * 512 + 64 * j, 64 * i, bars + i * 8);
            }
#pragma unroll
            for (int k = CH_W1; k < NCHUNK; k++) mbar_init(bars + k * 8, 1);
            asm volatile("fence.proxy.async.shared::cta;" ::: "memory");
        }
        __syncwarp();
        asm volatile("barrier.cluster.arrive.relaxed.aligned;" ::: "memory");
        bar_sync(1, NTHREADS);
        if (lane == 0) {
#pragma unroll
            for (int i = CH_W1; i < CH_WO; i++) {
                const uint32_t bar = bars + i * 8;
                const uint32_t dst = sb + slot_off(i);
                if (i >= WINDOW) mbar_wait(bar - WINDOW * 8);
                if (i >= NSLOT) mbar_wait(bars + (BAR_EMPTY + i - NSLOT) * 8);
                if (i < CH_K) {
                    const int q = i - CH_W1;
                    if (c < 112) {
                        mbar_expect_tx(bar, 8192);
                        tma2d(dst, &p.w1, 16 * c, 256 * q, bar);
                    } else {
                        mbar_expect_tx(bar, 0);
                    }
                } else if (i < CH_V) {
                    const int q = i - CH_K;
                    mbar_expect_tx(bar, 8192);
                    tma2d(dst, &p.k, 0, krow + q * 32, bar);
                    tma2d(dst + 4096, &p.k, 64, krow + q * 32, bar);
                } else {
                    const int q = i - CH_V;
                    mbar_expect_tx(bar, 8192);
                    tma2d(dst, &p.v, 0, krow + q * 32, bar);
                    tma2d(dst + 4096, &p.v, 64, krow + q * 32, bar);
                }
                TS(i);
            }
            if (GATE >= 0) mbar_wait(bars + (CH_V + GATE) * 8);
        }
        __syncwarp();
        asm volatile("barrier.cluster.wait.acquire.aligned;" ::: "memory");
        if (GATE >= 0 && lane < 8)
            asm volatile("mbarrier.arrive.relaxed.cluster.shared::cluster.b64 _, [%0];" ::"r"(mapa(bars + BAR_GATE * 8, lane)) : "memory");
        if (lane == 0) {
            if (GATE >= 0) mbar_wait(bars + BAR_GATE * 8);
#pragma unroll
            for (int i = CH_WO; i < NCHUNK; i++) {
                const uint32_t bar = bars + i * 8;
                const uint32_t dst = sb + slot_off(i);
                mbar_wait(bar - WINDOW * 8);
                mbar_wait(bars + (BAR_EMPTY + i - NSLOT) * 8);
                if (i < CH_W2) {
                    const int q = i - CH_WO;
                    mbar_expect_tx(bar, 8192);
                    tma2d(dst, &p.wo, 32 * g16, 512 * r + 128 * q, bar);
                } else {
                    const int q = i - CH_W2;
                    mbar_expect_tx(bar, 7168);
                    tma2d(dst, &p.w2, 32 * g16, 224 * r + 112 * q, bar);
                }
                TS(i - 24);
            }
        }
        return;
    }

    Scratch* const sc = p.sc;
    const float LOG2E = 1.4426950408889634f;

    if (warp == NCW + 1) {
        const uint32_t tag = *reinterpret_cast<volatile unsigned*>(&sc->epoch) + 1u;
        if (lane == 0) {
            mbar_init(bars + BAR_Q * 8, 1);
            mbar_init(bars + BAR_ST * 8, 1);
            mbar_init(bars + BAR_PO * 8, 1);
            mbar_init(bars + BAR_GATE * 8, 8);
            asm volatile("fence.mbarrier_init.release.cluster;" ::: "memory");
            mbar_expect_tx(bars + BAR_Q * 8, 1024);
            mbar_expect_tx(bars + BAR_ST * 8, 256);
            mbar_expect_tx(bars + BAR_PO * 8, 2048);
#pragma unroll
            for (int k = 0; k <= CH_V; k++) mbar_init(bars + (BAR_EMPTY + k) * 8, (k >= CH_K && k < CH_V) ? 1 : NCW);
        }
        __syncwarp();
        asm volatile("barrier.cluster.arrive.relaxed.aligned;" ::: "memory");
        if (lane == 0) sts_u1(sb + SM_EPOCH, tag);
        __syncwarp();
        bar_arrive(1, NTHREADS);
        TS(0);
        asm volatile("barrier.cluster.wait.acquire.aligned;" ::: "memory");
        bar_sync(4, NCT + 32);
        {
            float mx = lds_f1(sb + SM_MAX + lane * 4);
            float sm = lds_f1(sb + SM_SUM + lane * 4);
#pragma unroll
            for (int o = 4; o < 32; o <<= 1) { mx = fmaxf(mx, __shfl_xor_sync(~0u, mx, o)); sm += __shfl_xor_sync(~0u, sm, o); }
            const uint32_t dst = mapa(sb + SM_INS + (j * 4 + (lane & 3)) * 8, lane >> 2);
            const uint32_t rbar = mapa(bars + BAR_ST * 8, lane >> 2);
            asm volatile("st.async.weak.shared::cluster.mbarrier::complete_tx::bytes.v2.f32 [%0], {%1, %2}, [%3];"
                         ::"r"(dst), "f"(mx), "f"(sm), "r"(rbar) : "memory");
        }
        TS(2);
        float coef[8];
        {
            mbar_wait_cluster(bars + BAR_ST * 8);
            const float2 st = lds_f2(sb + SM_INS + lane * 8);
            float gm = st.x;
#pragma unroll
            for (int o = 4; o < 32; o <<= 1) gm = fmaxf(gm, __shfl_xor_sync(~0u, gm, o));
            const float wj = ex2((st.x - gm) * LOG2E);
            float gl = wj * st.y;
#pragma unroll
            for (int o = 4; o < 32; o <<= 1) gl += __shfl_xor_sync(~0u, gl, o);
            const float cj = wj / gl;
#pragma unroll
            for (int k = 0; k < 8; k++) coef[k] = __shfl_sync(~0u, cj, k * 4 + (lane >> 3));
        }
        TS(3);
        mbar_wait_cluster(bars + BAR_PO * 8);
        {
            float o0 = 0.f, o1 = 0.f;
#pragma unroll
            for (int k = 0; k < 8; k++) {
                const float2 v = lds_f2(sb + SM_INB + k * 256 + lane * 8);
                o0 = fmaf(coef[k], v.x, o0);
                o1 = fmaf(coef[k], v.y, o1);
            }
            const int head = (bh & 7) * 4 + (lane >> 3);
            st_ll1(&sc->ox[((bh >> 3) * 256 + head * 8 + j) * 8 + (lane & 7)], pack_bf16(o0, o1), tag);
        }
        TS(4);
        return;
    }

    const int u = warp;
    const int fg = lane >> 2, ft = lane & 3;
    asm volatile("barrier.cluster.arrive.relaxed.aligned;" ::: "memory");

    uint32_t xres = 0;
    uint32_t b1pair = 0;
    if (u < 2) {
        const uint4* x4 = reinterpret_cast<const uint4*>(p.x) + u * 64 + lane * 2;
        const uint4 v0 = __ldg(x4), v1 = __ldg(x4 + 1);
        if (u == 0) xres = __ldg(reinterpret_cast<const uint32_t*>(p.x) + (lane >> 4) * 256 + g16 * 16 + (lane & 15));
        if (u == 1 && c < 112) b1pair = __ldg(reinterpret_cast<const uint32_t*>(p.b1) + c * 8 + (lane & 7));
        const uint32_t a[8] = {v0.x, v0.y, v0.z, v0.w, v1.x, v1.y, v1.z, v1.w};
        float s0 = 0.f;
#pragma unroll
        for (int i = 0; i < 8; i++) s0 += bf_lo(a[i]) + bf_hi(a[i]);
#pragma unroll
        for (int o = 16; o > 0; o >>= 1) s0 += __shfl_xor_sync(~0u, s0, o);
        const float m0 = s0 * (1.f / D_MODEL);
        float q0 = 0.f;
#pragma unroll
        for (int i = 0; i < 8; i++) {
            float d;
            d = bf_lo(a[i]) - m0; q0 += d * d; d = bf_hi(a[i]) - m0; q0 += d * d;
        }
#pragma unroll
        for (int o = 16; o > 0; o >>= 1) q0 += __shfl_xor_sync(~0u, q0, o);
        const float mean = bf16r(m0);
        const float var = bf16r(q0 * (1.f / D_MODEL));
        const float den = bf16r(sqrtf(bf16r(var + 1e-5f)));
        const float rden = 1.f / den;
        uint32_t o[8];
#pragma unroll
        for (int i = 0; i < 8; i++) o[i] = pack_bf16(bf16r(bf_lo(a[i]) - mean) * rden, bf16r(bf_hi(a[i]) - mean) * rden);
        const uint32_t dst = sb + SM_XN + u * 1024 + lane * 32;
        sts_u4(dst, o[0], o[1], o[2], o[3]);
        sts_u4(dst + 16, o[4], o[5], o[6], o[7]);
        TS(0);
    }

    const int lrow = (lane & 7) + ((lane >> 4) << 3);
    const int lchk = (lane >> 3) & 1;

    bar_sync(1, NTHREADS);
    const uint32_t tag = lds_u1(sb + SM_EPOCH);

    {
        float acc[4] = {};
        const uint32_t xa = sb + SM_XN + (bh >> 3) * 1024 + ((u >> 2) * 16 + ft) * 4;
        const int row = (u >> 2) * 32 + lrow;
        const uint32_t wa = row * 128 + ((((u & 3) * 2 + lchk) ^ (row & 7)) << 4);
#pragma unroll
        for (int q = 0; q < 8; q++) {
            const uint32_t b0 = lds_u1(xa + q * 128), b1 = lds_u1(xa + q * 128 + 16), b2 = lds_u1(xa + q * 128 + 32),
                           b3 = lds_u1(xa + q * 128 + 48);
            mbar_wait(bars + (CH_WQ + q) * 8);
            uint32_t a0[4], a1[4];
            ldsm4t(a0, sb + slot_off(CH_WQ + q) + wa);
            ldsm4t(a1, sb + slot_off(CH_WQ + q) + wa + 2048);
            mma16816(acc, a0[0], a0[1], a0[2], a0[3], b0, b1);
            mma16816(acc, a1[0], a1[1], a1[2], a1[3], b2, b3);
            if (lane == 0) mbar_arrive(bars + (BAR_EMPTY + CH_WQ + q) * 8);
        }
        TS(1);
        if (ft == 0) {
            sts_f1(sb + SM_REDA + ((u >> 2) * 64 + (u & 3) * 16 + fg) * 4, acc[0]);
            sts_f1(sb + SM_REDA + ((u >> 2) * 64 + (u & 3) * 16 + fg + 8) * 4, acc[2]);
        }
    }
    asm volatile("barrier.cluster.wait.acquire.aligned;" ::: "memory");
    bar_sync(2, NCT);
    if (u == 0) {
        const float2 s0 = lds_f2(sb + SM_REDA + lane * 8), s1 = lds_f2(sb + SM_REDA + 256 + lane * 8);
        const uint32_t qp = pack_bf16(s0.x + s1.x, s0.y + s1.y);
        const uint32_t dst = sb + SM_Q + (((j >> 1) * 4 + (lane & 3)) * 16 + (j & 1) * 8 + (lane >> 2)) * 4;
#pragma unroll
        for (int k = 0; k < 8; k++)
            asm volatile("st.async.weak.shared::cluster.mbarrier::complete_tx::bytes.u32 [%0], %1, [%2];"
                         ::"r"(mapa(dst, k)), "r"(qp), "r"(mapa(bars + BAR_Q * 8, k)) : "memory");
        TS(2);
    }

    if (c < 112) {
        uint32_t xb[4][2];
#pragma unroll
        for (int q = 0; q < 4; q++) {
            xb[q][0] = lds_u1(sb + SM_XN + (fg & 1) * 1024 + (q * 64 + u * 8 + ft) * 4);
            xb[q][1] = lds_u1(sb + SM_XN + (fg & 1) * 1024 + (q * 64 + u * 8 + 4 + ft) * 4);
        }
        float acc[4] = {};
#pragma unroll
        for (int q = 0; q < 4; q++) {
            if ((q & 1) == 0) mbar_wait(bars + (CH_W1 + (q >> 1)) * 8);
            const int row = (q & 1) * 128 + u * 16 + lrow;
            uint32_t a[4];
            ldsm4t(a, sb + slot_off(CH_W1 + (q >> 1)) + row * 32 + ((lchk ^ ((row >> 2) & 1)) << 4));
            mma16816(acc, a[0], a[1], a[2], a[3], xb[q][0], xb[q][1]);
            if ((q & 1) && lane == 0) mbar_arrive(bars + (BAR_EMPTY + CH_W1 + (q >> 1)) * 8);
        }
        TS(10);
        if (ft == 0) {
            const uint32_t rb = sb + SM_REDB + u * 128;
            sts_f1(rb + fg * 4, acc[0]);
            sts_f1(rb + 64 + fg * 4, acc[1]);
            sts_f1(rb + (fg + 8) * 4, acc[2]);
            sts_f1(rb + 64 + (fg + 8) * 4, acc[3]);
        }
        bar_sync(2, NCT);
        if (u == 1 && lane < 16) {
            float2 s = make_float2(0.f, 0.f);
#pragma unroll
            for (int k = 0; k < NCW; k++) {
                float2 v = lds_f2(sb + SM_REDB + k * 128 + lane * 8);
                s.x += v.x; s.y += v.y;
            }
            float h[2] = {bf16r(bf16r(s.x) + bf_lo(b1pair)), bf16r(bf16r(s.y) + bf_hi(b1pair))};
            float a[2];
#pragma unroll
            for (int i = 0; i < 2; i++) {
                const float e = bf16r(__expf(-fabsf(h[i])));
                const float sp = bf16r(bf16r(log1pf(e)) + fmaxf(h[i], 0.f));
                a[i] = h[i] * bf16r(tanhf(sp));
            }
            const int dp = lane & 7;
            st_ll1(&sc->ax[(((lane >> 3) * 112 + c) * 4 + (dp & 3)) * 2 + (dp >> 2)], pack_bf16(a[0], a[1]), tag);
            TS(11);
        }
    } else if (lane == 0) {
        mbar_arrive(bars + (BAR_EMPTY + CH_W1) * 8);
        mbar_arrive(bars + (BAR_EMPTY + CH_W1 + 1) * 8);
    }
    __syncwarp();

    {
        mbar_wait_cluster(bars + BAR_Q * 8);
        TS(3);
        uint32_t qa[16];
#pragma unroll
        for (int i = 0; i < 4; i++) lds_u4(qa + 4 * i, sb + SM_Q + ((fg & 3) * 4 + ft) * 64 + i * 16);
        mbar_wait(bars + (CH_K + u) * 8);
        TS(4);
        float acc[4][4] = {};
        const uint32_t kb = sb + ((CH_K + u) % NSLOT) * 8192 + (lane & 7) * 128;
#pragma unroll
        for (int q = 0; q < 4; q++) {
            const int chunk = q * 4 + (lane >> 3);
            const uint32_t off = (chunk >> 3) * 4096 + (((chunk & 7) ^ (lane & 7)) << 4);
#pragma unroll
            for (int nt = 0; nt < 4; nt++) {
                uint32_t b[4];
                ldsm4(b, kb + nt * 1024 + off);
                mma16816(acc[nt], qa[4 * q], 0u, qa[4 * q + 1], 0u, b[0], b[1]);
                mma16816(acc[nt], qa[4 * q + 2], 0u, qa[4 * q + 3], 0u, b[2], b[3]);
            }
        }
        if (lane == 0) mbar_arrive(bars + (BAR_EMPTY + CH_K + u) * 8);
        const float scale = 0.08838834764831845f;
        float sv[8];
#pragma unroll
        for (int i = 0; i < 8; i++) sv[i] = bf16r(bf16r(acc[i >> 1][i & 1]) * scale);
        float m = fmaxf(fmaxf(fmaxf(sv[0], sv[1]), fmaxf(sv[2], sv[3])), fmaxf(fmaxf(sv[4], sv[5]), fmaxf(sv[6], sv[7])));
        m = fmaxf(m, __shfl_xor_sync(~0u, m, 1));
        m = fmaxf(m, __shfl_xor_sync(~0u, m, 2));
        if (lane < 16 && ft == 0) sts_f1(sb + SM_MAX + (u * 4 + fg) * 4, m);
        TS(5);
        bar_sync(2, NCT);
        m = lds_f1(sb + SM_MAX + ((ft + 4 * (fg >> 2)) * 4 + (fg & 3)) * 4);
        m = fmaxf(m, __shfl_xor_sync(~0u, m, 1));
        m = fmaxf(m, __shfl_xor_sync(~0u, m, 2));
        m = fmaxf(m, __shfl_xor_sync(~0u, m, 16));
#pragma unroll
        for (int i = 0; i < 8; i++) sv[i] = ex2((sv[i] - m) * LOG2E);
        float l = ((sv[0] + sv[1]) + (sv[2] + sv[3])) + ((sv[4] + sv[5]) + (sv[6] + sv[7]));
        l += __shfl_xor_sync(~0u, l, 1);
        l += __shfl_xor_sync(~0u, l, 2);
        if (lane < 16) {
            sts_u4(sb + SM_P + (u * 16 + lane) * 16, pack_bf16(sv[0], sv[1]), pack_bf16(sv[2], sv[3]), pack_bf16(sv[4], sv[5]),
                   pack_bf16(sv[6], sv[7]));
            if (ft == 0) sts_f1(sb + SM_SUM + (u * 4 + fg) * 4, l);
        }
        bar_sync(4, NCT + 32);
        TS(6);
    }

    unsigned long long w[6][2] = {};
    const unsigned long long* so = &sc->ox[(((fg & 1) * 256 + r * 32 + u) * 4 + ft) * 2];
    const unsigned long long* sa = &sc->ax[(((fg & 1) * 112 + r * 14 + (u < 7 ? u : 0)) * 4 + ft) * 2];
    {
        float acc[2][4] = {};
        const uint32_t voff = (u >> 2) * 4096 + lane * 128;
        const uint32_t c0 = (((u & 3) * 2) ^ (lane & 7)) << 4, c1 = (((u & 3) * 2 + 1) ^ (lane & 7)) << 4;
#pragma unroll
        for (int i = 0; i < 8; i++) {
            uint32_t pa[4], b0[4], b1[4];
            lds_u4(pa, sb + SM_P + (i * 16 + (lane & 15)) * 16);
            mbar_wait(bars + (CH_V + i) * 8);
            ldsm4t(b0, sb + slot_off(CH_V + i) + voff + c0);
            ldsm4t(b1, sb + slot_off(CH_V + i) + voff + c1);
            mma16816(acc[0], pa[0], 0u, pa[1], 0u, b0[0], b0[1]);
            mma16816(acc[1], pa[0], 0u, pa[1], 0u, b1[0], b1[1]);
            mma16816(acc[0], pa[2], 0u, pa[3], 0u, b0[2], b0[3]);
            mma16816(acc[1], pa[2], 0u, pa[3], 0u, b1[2], b1[3]);
            if (i == 0 && lane == 0) mbar_arrive(bars + (BAR_EMPTY + CH_V) * 8);
        }
        TS(8);
        if (lane < 16) {
            const uint32_t dst = mapa(sb + SM_INB + j * 256 + lane * 16, u);
            const uint32_t rbar = mapa(bars + BAR_PO * 8, u);
            asm volatile("st.async.weak.shared::cluster.mbarrier::complete_tx::bytes.v4.f32 [%0], {%1, %2, %3, %4}, [%5];"
                         ::"r"(dst), "f"(acc[0][0]), "f"(acc[0][1]), "f"(acc[1][0]), "f"(acc[1][1]), "r"(rbar) : "memory");
        }
        TS(9);
    }

    {
        unsigned long long v[7][2] = {};
        const unsigned long long* psrc = &sc->px[(g16 * 8 + 1) * 64 + lane * 2];
        if (u == 0 && r == 0) {
#pragma unroll
            for (int i = 0; i < 7; i++) ld_ll2(psrc + i * 64, v[i][0], v[i][1]);
        }
        uint32_t wa[4][2][4];
        const int row = u * 16 + lrow;
        const uint32_t ro0 = row * 64 + ((lchk ^ ((row >> 1) & 3)) << 4), ro1 = row * 64 + (((2 + lchk) ^ ((row >> 1) & 3)) << 4);
        auto poll = [&](int lo, int hi) {
            if (lane < 8) {
                unsigned n = 0;
                while (true) {
#pragma unroll
                    for (int q = 0; q < 6; q++)
                        if (q >= lo && q < hi && !tag_ok(w[q][0], w[q][1], tag))
                            ld_ll2(q < 4 ? so + q * 64 : sa + (q - 4) * 56, w[q][0], w[q][1]);
                    bool ok = true;
#pragma unroll
                    for (int q = 0; q < 6; q++)
                        if (q >= lo && q < hi) ok = ok && tag_ok(w[q][0], w[q][1], tag);
                    if (ok || ++n >= SPIN_LIMIT) break;
                    __nanosleep(20);
                }
            }
            __syncwarp();
        };
        poll(4, 6);
#pragma unroll
        for (int q = 0; q < 4; q++) {
            mbar_wait(bars + (CH_WO + q) * 8);
            ldsm4t(wa[q][0], sb + slot_off(CH_WO + q) + ro0);
            ldsm4t(wa[q][1], sb + slot_off(CH_WO + q) + ro1);
        }
        TS(12);
        poll(0, 4);
        TS(13);
        float acc[2][4] = {}, acc2[2][4] = {};
#pragma unroll
        for (int q = 0; q < 4; q += 2) {
#pragma unroll
            for (int mt = 0; mt < 2; mt++) {
                mma16816(acc[mt], wa[q][mt][0], wa[q][mt][1], wa[q][mt][2], wa[q][mt][3], (uint32_t)w[q][0], (uint32_t)w[q][1]);
                mma16816(acc2[mt], wa[q + 1][mt][0], wa[q + 1][mt][1], wa[q + 1][mt][2], wa[q + 1][mt][3], (uint32_t)w[q + 1][0],
                         (uint32_t)w[q + 1][1]);
            }
        }
        if (u < 7) {
            mbar_wait(bars + CH_W2 * 8);
            gemv_tile64(acc, sb + slot_off(CH_W2), row, lchk, (uint32_t)w[4][0], (uint32_t)w[4][1]);
            mbar_wait(bars + (CH_W2 + 1) * 8);
            gemv_tile64(acc2, sb + slot_off(CH_W2 + 1), row, lchk, (uint32_t)w[5][0], (uint32_t)w[5][1]);
        }
#pragma unroll
        for (int mt = 0; mt < 2; mt++)
#pragma unroll
            for (int i = 0; i < 4; i++) acc[mt][i] += acc2[mt][i];
        TS(14);
        if (ft == 0) {
            const uint32_t rb = sb + SM_REDO + u * 256;
#pragma unroll
            for (int mt = 0; mt < 2; mt++) {
                sts_f1(rb + (mt * 16 + fg) * 4, acc[mt][0]);
                sts_f1(rb + 128 + (mt * 16 + fg) * 4, acc[mt][1]);
                sts_f1(rb + (mt * 16 + fg + 8) * 4, acc[mt][2]);
                sts_f1(rb + 128 + (mt * 16 + fg + 8) * 4, acc[mt][3]);
            }
        }
        if (u != 0) { bar_arrive(2, NCT); return; }
        bar_sync(2, NCT);
        float2 s = make_float2(0.f, 0.f);
#pragma unroll
        for (int k = 0; k < NCW; k++) {
            float2 t = lds_f2(sb + SM_REDO + k * 256 + lane * 8);
            s.x += t.x; s.y += t.y;
        }
        if (r != 0) {
            st_ll2(&sc->px[(g16 * 8 + r) * 64 + lane * 2], __float_as_uint(s.x), __float_as_uint(s.y), tag);
            TS(15);
            return;
        }
        TS(15);
        unsigned n = 0;
        while (true) {
#pragma unroll
            for (int i = 0; i < 7; i++)
                if (!tag_ok(v[i][0], v[i][1], tag)) ld_ll2(psrc + i * 64, v[i][0], v[i][1]);
            bool ok = true;
#pragma unroll
            for (int i = 0; i < 7; i++) ok = ok && tag_ok(v[i][0], v[i][1], tag);
            if (ok || ++n >= SPIN_LIMIT) break;
        }
#pragma unroll
        for (int i = 0; i < 7; i++) { s.x += __uint_as_float((uint32_t)v[i][0]); s.y += __uint_as_float((uint32_t)v[i][1]); }
        reinterpret_cast<uint32_t*>(p.out)[(lane >> 4) * 256 + g16 * 16 + (lane & 15)] =
            pack_bf16(bf_lo(xres) + s.x, bf_hi(xres) + s.y);
        __syncwarp();
        if (c == 0 && lane == 0) sc->epoch = tag;
        TS(16);
    }
}

typedef CUresult (*EncodeTiledFn)(CUtensorMap*, CUtensorMapDataType, cuuint32_t, void*, const cuuint64_t*, const cuuint64_t*,
                                  const cuuint32_t*, const cuuint32_t*, CUtensorMapInterleave, CUtensorMapSwizzle,
                                  CUtensorMapL2promotion, CUtensorMapFloatOOBfill);

void make_map(EncodeTiledFn enc, CUtensorMap* m, const void* base, uint64_t cols, uint64_t rows, uint32_t box_c, uint32_t box_r,
              CUtensorMapSwizzle sw) {
    cuuint64_t gd[2] = {cols, rows};
    cuuint64_t gs[1] = {cols * 2};
    cuuint32_t bd[2] = {box_c, box_r};
    cuuint32_t es[2] = {1, 1};
    enc(m, CU_TENSOR_MAP_DATA_TYPE_BFLOAT16, 2, const_cast<void*>(base), gd, gs, bd, es, CU_TENSOR_MAP_INTERLEAVE_NONE, sw,
        CU_TENSOR_MAP_L2_PROMOTION_L2_128B, CU_TENSOR_MAP_FLOAT_OOB_FILL_NONE);
}

}

extern "C" void kernel_launch(void* const* d_in, const int* in_sizes, int n_in, void* d_out, int out_size) {
    (void)in_sizes; (void)n_in; (void)out_size;
    static EncodeTiledFn enc = nullptr;
    static Scratch* sc = nullptr;
    if (!enc) {
        void* fn = nullptr;
        cudaDriverEntryPointQueryResult st;
        cudaGetDriverEntryPoint("cuTensorMapEncodeTiled", &fn, cudaEnableDefault, &st);
        enc = (EncodeTiledFn)fn;
        cudaFuncSetAttribute(fused_decode_kernel, cudaFuncAttributeMaxDynamicSharedMemorySize, SM_TOTAL);
        void* sp = nullptr;
        cudaGetSymbolAddress(&sp, g_scratch);
        sc = (Scratch*)sp;
    }
    Params p;
    make_map(enc, &p.k, d_in[1], 128, 2 * 8 * SK, 64, 32, CU_TENSOR_MAP_SWIZZLE_128B);
    make_map(enc, &p.v, d_in[2], 128, 2 * 8 * SK, 64, 32, CU_TENSOR_MAP_SWIZZLE_128B);
    make_map(enc, &p.wq, d_in[3], 4096, 512, 64, 64, CU_TENSOR_MAP_SWIZZLE_128B);
    make_map(enc, &p.wo, d_in[4], 512, 4096, 32, 128, CU_TENSOR_MAP_SWIZZLE_64B);
    make_map(enc, &p.w1, d_in[6], FF, 512, 16, 256, CU_TENSOR_MAP_SWIZZLE_32B);
    make_map(enc, &p.w2, d_in[8], 512, FF, 32, 112, CU_TENSOR_MAP_SWIZZLE_64B);
    p.x = (const __nv_bfloat16*)d_in[0];
    p.b1 = (const __nv_bfloat16*)d_in[7];
    p.out = (__nv_bfloat16*)d_out;
    p.sc = sc;
    fused_decode_kernel<<<NCTA, NTHREADS, SM_TOTAL, cudaStreamPerThread>>>(p);
}
```

```cpp
#include <cuda_runtime.h>
#include <cuda_bf16.h>
#include <cuda.h>
#include <stdint.h>

namespace {

constexpr int D_MODEL = 512;
constexpr int SK = 8192;
constexpr int WIN = 2048;
constexpr int WIN0 = SK - WIN;
constexpr int FF = 1792;

constexpr int NCTA = 128;
constexpr int NCW = 8;
constexpr int NCT = NCW * 32;
constexpr int NTHREADS = (NCW + 2) * 32;

constexpr int CH_WQ = 0, CH_W1 = 8, CH_K = 10, CH_V = 18, CH_W2 = 26, CH_WO = 28, NCHUNK = 36;
constexpr int NSLOT = 13;
constexpr int NEMPTY = NCHUNK - NSLOT;
#define WINDOW 8
__host__ __device__ constexpr int slot_off(int chunk) { return (chunk % NSLOT) * 8192; }

constexpr int BAR_FULL = 0;
constexpr int BAR_EMPTY = NCHUNK;
constexpr int BAR_Q = BAR_EMPTY + NEMPTY;
constexpr int BAR_ST = BAR_Q + 1;
constexpr int BAR_PO = BAR_ST + 1;
constexpr int BAR_O = BAR_PO + 1;
constexpr int NBAR = BAR_O + 1;

constexpr int SM_RING = 0;
constexpr int SM_INB = NSLOT * 8192;
constexpr int SM_INS = SM_INB + 2048;
constexpr int SM_REDA = SM_INS + 256;
constexpr int SM_REDG = SM_REDA + 512;
constexpr int SM_REDB = SM_REDA + 2048;
constexpr int SM_XN = SM_REDB + 1024;
constexpr int SM_P = SM_XN;
constexpr int SM_Q = SM_XN + 2048;
constexpr int SM_O = SM_Q;
constexpr int SM_MAX = SM_Q + 1024;
constexpr int SM_SUM = SM_MAX + 128;
constexpr int SM_BAR = SM_SUM + 128;
constexpr int SM_EPOCH = SM_BAR + NBAR * 8;
constexpr int SM_TOTAL = SM_EPOCH + 8;
static_assert(SM_TOTAL <= 115712, "two CTAs must fit on one SM");

constexpr unsigned SPIN_LIMIT = 1u << 22;

struct Scratch {
    unsigned epoch;
    unsigned pad[31];
    unsigned long long ax[2 * 112 * 8];
    unsigned long long pf[16 * 8 * 64];
    unsigned long long pa[16 * 8 * 64];
};

__device__ Scratch g_scratch;

struct Params {
    CUtensorMap wq, k, v, w1, wo, w2;
    const __nv_bfloat16* x;
    const __nv_bfloat16* b1;
    __nv_bfloat16* out;
    Scratch* sc;
};

__device__ __forceinline__ uint32_t smem_u32(const void* p) { return (uint32_t)__cvta_generic_to_shared(p); }
__device__ __forceinline__ void mbar_init(uint32_t bar, uint32_t cnt) {
    asm volatile("mbarrier.init.shared::cta.b64 [%0], %1;" ::"r"(bar), "r"(cnt) : "memory");
}
__device__ __forceinline__ void mbar_expect_tx(uint32_t bar, uint32_t bytes) {
    asm volatile("mbarrier.arrive.expect_tx.shared::cta.b64 _, [%0], %1;" ::"r"(bar), "r"(bytes) : "memory");
}
__device__ __forceinline__ void mbar_arrive(uint32_t bar) {
    asm volatile("mbarrier.arrive.shared::cta.b64 _, [%0];" ::"r"(bar) : "memory");
}
__device__ __forceinline__ void mbar_wait(uint32_t bar) {
    unsigned n = 0;
    uint32_t ok;
    do {
        asm volatile("{\n.reg .pred p;\nmbarrier.try_wait.parity.shared::cta.b64 p, [%1], 0;\nselp.u32 %0, 1, 0, p;\n}"
                     : "=r"(ok) : "r"(bar) : "memory");
    } while (!ok && ++n < SPIN_LIMIT);
}
__device__ __forceinline__ void mbar_wait_cluster(uint32_t bar) {
    unsigned n = 0;
    uint32_t ok;
    do {
        asm volatile("{\n.reg .pred p;\nmbarrier.try_wait.parity.acquire.cluster.shared::cta.b64 p, [%1], 0;\nselp.u32 %0, 1, 0, p;\n}"
                     : "=r"(ok) : "r"(bar) : "memory");
    } while (!ok && ++n < SPIN_LIMIT);
}
__device__ __forceinline__ void tma2d(uint32_t dst, const CUtensorMap* tm, int c0, int c1, uint32_t bar) {
    asm volatile("cp.async.bulk.tensor.2d.shared::cluster.global.mbarrier::complete_tx::bytes [%0], [%1, {%3, %4}], [%2];"
                 ::"r"(dst), "l"((uint64_t)tm), "r"(bar), "r"(c0), "r"(c1) : "memory");
}
__device__ __forceinline__ uint32_t mapa(uint32_t addr, uint32_t rank) {
    uint32_t r;
    asm("mapa.shared::cluster.u32 %0, %1, %2;" : "=r"(r) : "r"(addr), "r"(rank));
    return r;
}
__device__ __forceinline__ void bar_sync(int id, int n) { asm volatile("bar.sync %0, %1;" ::"r"(id), "r"(n) : "memory"); }
__device__ __forceinline__ void bar_arrive(int id, int n) { asm volatile("bar.arrive %0, %1;" ::"r"(id), "r"(n) : "memory"); }

__device__ __forceinline__ void ldsm4(uint32_t (&r)[4], uint32_t addr) {
    asm volatile("ldmatrix.sync.aligned.m8n8.x4.shared.b16 {%0,%1,%2,%3}, [%4];"
                 : "=r"(r[0]), "=r"(r[1]), "=r"(r[2]), "=r"(r[3]) : "r"(addr) : "memory");
}
__device__ __forceinline__ void ldsm4t(uint32_t (&r)[4], uint32_t addr) {
    asm volatile("ldmatrix.sync.aligned.m8n8.x4.trans.shared.b16 {%0,%1,%2,%3}, [%4];"
                 : "=r"(r[0]), "=r"(r[1]), "=r"(r[2]), "=r"(r[3]) : "r"(addr) : "memory");
}
__device__ __forceinline__ void mma16816(float (&c)[4], uint32_t a0, uint32_t a1, uint32_t a2, uint32_t a3, uint32_t b0, uint32_t b1) {
    asm volatile("mma.sync.aligned.m16n8k16.row.col.f32.bf16.bf16.f32 {%0,%1,%2,%3}, {%4,%5,%6,%7}, {%8,%9}, {%0,%1,%2,%3};"
                 : "+f"(c[0]), "+f"(c[1]), "+f"(c[2]), "+f"(c[3])
                 : "r"(a0), "r"(a1), "r"(a2), "r"(a3), "r"(b0), "r"(b1));
}
__device__ __forceinline__ void st_ll1(unsigned long long* p, uint32_t d, uint32_t tag) {
    unsigned long long w = ((unsigned long long)tag << 32) | d;
    asm volatile("st.relaxed.gpu.global.b64 [%0], %1;" ::"l"(p), "l"(w) : "memory");
}
__device__ __forceinline__ void st_ll2(unsigned long long* p, uint32_t d0, uint32_t d1, uint32_t tag) {
    unsigned long long w0 = ((unsigned long long)tag << 32) | d0, w1 = ((unsigned long long)tag << 32) | d1;
    asm volatile("st.relaxed.gpu.global.v2.b64 [%0], {%1, %2};" ::"l"(p), "l"(w0), "l"(w1) : "memory");
}
__device__ __forceinline__ void ld_ll2(const unsigned long long* p, unsigned long long& w0, unsigned long long& w1) {
    asm volatile("ld.relaxed.gpu.global.v2.b64 {%0, %1}, [%2];" : "=l"(w0), "=l"(w1) : "l"(p) : "memory");
}
__device__ __forceinline__ bool tag_ok(unsigned long long w0, unsigned long long w1, uint32_t tag) {
    return (uint32_t)(w0 >> 32) == tag && (uint32_t)(w1 >> 32) == tag;
}
__device__ __forceinline__ float ex2(float x) {
    float y;
    asm("ex2.approx.ftz.f32 %0, %1;" : "=f"(y) : "f"(x));
    return y;
}
__device__ __forceinline__ float bf16r(float x) { return __bfloat162float(__float2bfloat16_rn(x)); }
__device__ __forceinline__ uint32_t pack_bf16(float lo, float hi) {
    __nv_bfloat162 v = __floats2bfloat162_rn(lo, hi);
    return *reinterpret_cast<uint32_t*>(&v);
}
__device__ __forceinline__ float bf_lo(uint32_t u) { return __uint_as_float(u << 16); }
__device__ __forceinline__ float bf_hi(uint32_t u) { return __uint_as_float(u & 0xffff0000u); }
__device__ __forceinline__ float2 lds_f2(uint32_t a) {
    float2 v;
    asm volatile("ld.shared.v2.f32 {%0, %1}, [%2];" : "=f"(v.x), "=f"(v.y) : "r"(a) : "memory");
    return v;
}
__device__ __forceinline__ float lds_f1(uint32_t a) {
    float v;
    asm volatile("ld.shared.f32 %0, [%1];" : "=f"(v) : "r"(a) : "memory");
    return v;
}
__device__ __forceinline__ uint32_t lds_u1(uint32_t a) {
    uint32_t v;
    asm volatile("ld.shared.u32 %0, [%1];" : "=r"(v) : "r"(a) : "memory");
    return v;
}
__device__ __forceinline__ void lds_u4(uint32_t* r, uint32_t a) {
    asm volatile("ld.shared.v4.u32 {%0,%1,%2,%3}, [%4];" : "=r"(r[0]), "=r"(r[1]), "=r"(r[2]), "=r"(r[3]) : "r"(a) : "memory");
}
__device__ __forceinline__ float4 lds_f4(uint32_t a) {
    float4 v;
    asm volatile("ld.shared.v4.f32 {%0,%1,%2,%3}, [%4];" : "=f"(v.x), "=f"(v.y), "=f"(v.z), "=f"(v.w) : "r"(a) : "memory");
    return v;
}
__device__ __forceinline__ void sts_f2(uint32_t a, float x, float y) {
    asm volatile("st.shared.v2.f32 [%0], {%1, %2};" ::"r"(a), "f"(x), "f"(y) : "memory");
}
__device__ __forceinline__ void sts_f4(uint32_t a, float x, float y, float z, float w) {
    asm volatile("st.shared.v4.f32 [%0], {%1,%2,%3,%4};" ::"r"(a), "f"(x), "f"(y), "f"(z), "f"(w) : "memory");
}
__device__ __forceinline__ void sts_f1(uint32_t a, float v) { asm volatile("st.shared.f32 [%0], %1;" ::"r"(a), "f"(v) : "memory"); }
__device__ __forceinline__ void sts_u1(uint32_t a, uint32_t v) { asm volatile("st.shared.u32 [%0], %1;" ::"r"(a), "r"(v) : "memory"); }
__device__ __forceinline__ void sts_u4(uint32_t a, uint32_t x, uint32_t y, uint32_t z, uint32_t w) {
    asm volatile("st.shared.v4.u32 [%0], {%1,%2,%3,%4};" ::"r"(a), "r"(x), "r"(y), "r"(z), "r"(w) : "memory");
}

#define TS(i) do { } while (0)

__device__ __forceinline__ void gemv_tile64(float (&acc)[2][4], uint32_t base, int row, int lchk, uint32_t b0, uint32_t b1) {
    uint32_t a0[4], a1[4];
    const uint32_t ra = base + row * 64;
    const int sw = (row >> 1) & 3;
    ldsm4t(a0, ra + ((lchk ^ sw) << 4));
    ldsm4t(a1, ra + (((2 + lchk) ^ sw) << 4));
    mma16816(acc[0], a0[0], a0[1], a0[2], a0[3], b0, b1);
    mma16816(acc[1], a1[0], a1[1], a1[2], a1[3], b0, b1);
}

__global__ void __cluster_dims__(8, 1, 1) __launch_bounds__(NTHREADS, 2) fused_decode_kernel(const __grid_constant__ Params p) {
    extern __shared__ __align__(1024) uint8_t smem[];
    const uint32_t sb = smem_u32(smem);
    const uint32_t bars = sb + SM_BAR;
    const int c = blockIdx.x;
    const int warp = threadIdx.x >> 5, lane = threadIdx.x & 31;
    const int bh = c >> 3, j = c & 7;
    const int r = c >> 4, g16 = c & 15;

    if (warp == NCW) {
        const int krow = bh * SK + WIN0 + j * 256;
        if (lane == 0) {
#pragma unroll
            for (int i = 0; i < CH_W1; i++) mbar_init(bars + i * 8, 1);
            asm volatile("fence.proxy.async.shared::cta;" ::: "memory");
#pragma unroll
            for (int i = 0; i < CH_W1; i++) {
                mbar_expect_tx(bars + i * 8, 8192);
                tma2d(sb + slot_off(i), &p.wq, (bh & 7) * 512 + 64 * j, 64 * i, bars + i * 8);
            }
#pragma unroll
            for (int k = CH_W1; k < NCHUNK; k++) mbar_init(bars + k * 8, 1);
            asm volatile("fence.proxy.async.shared::cta;" ::: "memory");
        }
        __syncwarp();
        asm volatile("barrier.cluster.arrive.relaxed.aligned;" ::: "memory");
        bar_sync(1, NTHREADS);
        if (lane == 0) {
#pragma unroll
            for (int i = CH_W1; i < NCHUNK; i++) {
                const uint32_t bar = bars + i * 8;
                const uint32_t dst = sb + slot_off(i);
                if (i >= WINDOW) mbar_wait(bar - WINDOW * 8);
                if (i >= NSLOT) mbar_wait(bars + (BAR_EMPTY + i - NSLOT) * 8);
                if (i < CH_K) {
                    const int q = i - CH_W1;
                    if (c < 112) {
                        mbar_expect_tx(bar, 8192);
                        tma2d(dst, &p.w1, 16 * c, 256 * q, bar);
                    } else {
                        mbar_expect_tx(bar, 0);
                    }
                } else if (i < CH_V) {
                    const int q = i - CH_K;
                    mbar_expect_tx(bar, 8192);
                    tma2d(dst, &p.k, 0, krow + q * 32, bar);
                    tma2d(dst + 4096, &p.k, 64, krow + q * 32, bar);
                } else if (i < CH_W2) {
                    const int q = i - CH_V;
                    mbar_expect_tx(bar, 8192);
                    tma2d(dst, &p.v, 0, krow + q * 32, bar);
                    tma2d(dst + 4096, &p.v, 64, krow + q * 32, bar);
                } else if (i < CH_WO) {
                    const int q = i - CH_W2;
                    mbar_expect_tx(bar, 7168);
                    tma2d(dst, &p.w2, 32 * g16, 224 * r + 112 * q, bar);
                } else {
                    const int q = i - CH_WO;
                    mbar_expect_tx(bar, 8192);
                    tma2d(dst, &p.wo, 64 * j, 512 * (bh & 7) + 64 * q, bar);
                }
            }
        }
        return;
    }

    Scratch* const sc = p.sc;
    const float LOG2E = 1.4426950408889634f;

    if (warp == NCW + 1) {
        const uint32_t tag = *reinterpret_cast<volatile unsigned*>(&sc->epoch) + 1u;
        if (lane == 0) {
            mbar_init(bars + BAR_Q * 8, 1);
            mbar_init(bars + BAR_ST * 8, 1);
            mbar_init(bars + BAR_PO * 8, 1);
            mbar_init(bars + BAR_O * 8, 1);
            asm volatile("fence.mbarrier_init.release.cluster;" ::: "memory");
            mbar_expect_tx(bars + BAR_Q * 8, 1024);
            mbar_expect_tx(bars + BAR_ST * 8, 256);
            mbar_expect_tx(bars + BAR_PO * 8, 2048);
            mbar_expect_tx(bars + BAR_O * 8, 1024);
#pragma unroll
            for (int k = 0; k < NEMPTY; k++) mbar_init(bars + (BAR_EMPTY + k) * 8, (k >= CH_K && k < CH_V) ? 1 : NCW);
        }
        __syncwarp();
        asm volatile("barrier.cluster.arrive.relaxed.aligned;" ::: "memory");
        if (lane == 0) sts_u1(sb + SM_EPOCH, tag);
        __syncwarp();
        bar_arrive(1, NTHREADS);
        TS(0);
        asm volatile("barrier.cluster.wait.acquire.aligned;" ::: "memory");
        bar_sync(4, NCT + 32);
        {
            float mx = lds_f1(sb + SM_MAX + lane * 4);
            float sm = lds_f1(sb + SM_SUM + lane * 4);
#pragma unroll
            for (int o = 4; o < 32; o <<= 1) { mx = fmaxf(mx, __shfl_xor_sync(~0u, mx, o)); sm += __shfl_xor_sync(~0u, sm, o); }
            const uint32_t dst = mapa(sb + SM_INS + (j * 4 + (lane & 3)) * 8, lane >> 2);
            const uint32_t rbar = mapa(bars + BAR_ST * 8, lane >> 2);
            asm volatile("st.async.weak.shared::cluster.mbarrier::complete_tx::bytes.v2.f32 [%0], {%1, %2}, [%3];"
                         ::"r"(dst), "f"(mx), "f"(sm), "r"(rbar) : "memory");
        }
        TS(2);
        float coef[8];
        {
            mbar_wait_cluster(bars + BAR_ST * 8);
            const float2 st = lds_f2(sb + SM_INS + lane * 8);
            float gm = st.x;
#pragma unroll
            for (int o = 4; o < 32; o <<= 1) gm = fmaxf(gm, __shfl_xor_sync(~0u, gm, o));
            const float wj = ex2((st.x - gm) * LOG2E);
            float gl = wj * st.y;
#pragma unroll
            for (int o = 4; o < 32; o <<= 1) gl += __shfl_xor_sync(~0u, gl, o);
            const float cj = wj / gl;
#pragma unroll
            for (int k = 0; k < 8; k++) coef[k] = __shfl_sync(~0u, cj, k * 4 + (lane >> 3));
        }
        TS(3);
        mbar_wait_cluster(bars + BAR_PO * 8);
        {
            float o0 = 0.f, o1 = 0.f;
#pragma unroll
            for (int k = 0; k < 8; k++) {
                const float2 v = lds_f2(sb + SM_INB + k * 256 + lane * 8);
                o0 = fmaf(coef[k], v.x, o0);
                o1 = fmaf(coef[k], v.y, o1);
            }
            const uint32_t op = pack_bf16(o0, o1);
            const uint32_t dst = sb + SM_O + ((lane >> 3) * 64 + j * 8 + (lane & 1) * 4 + ((lane >> 1) & 3)) * 4;
#pragma unroll
            for (int k = 0; k < 8; k++)
                asm volatile("st.async.weak.shared::cluster.mbarrier::complete_tx::bytes.u32 [%0], %1, [%2];"
                             ::"r"(mapa(dst, k)), "r"(op), "r"(mapa(bars + BAR_O * 8, k)) : "memory");
        }
        TS(4);
        return;
    }

    const int u = warp;
    const int fg = lane >> 2, ft = lane & 3;
    asm volatile("barrier.cluster.arrive.relaxed.aligned;" ::: "memory");

    uint32_t xres = 0;
    uint32_t b1pair = 0;
    if (u < 2) {
        const uint4* x4 = reinterpret_cast<const uint4*>(p.x) + u * 64 + lane * 2;
        const uint4 v0 = __ldg(x4), v1 = __ldg(x4 + 1);
        if (u == 0) xres = __ldg(reinterpret_cast<const uint32_t*>(p.x) + (bh >> 3) * 256 + j * 32 + lane);
        if (u == 1 && c < 112) b1pair = __ldg(reinterpret_cast<const uint32_t*>(p.b1) + c * 8 + (lane & 7));
        const uint32_t a[8] = {v0.x, v0.y, v0.z, v0.w, v1.x, v1.y, v1.z, v1.w};
        float s0 = 0.f;
#pragma unroll
        for (int i = 0; i < 8; i++) s0 += bf_lo(a[i]) + bf_hi(a[i]);
#pragma unroll
        for (int o = 16; o > 0; o >>= 1) s0 += __shfl_xor_sync(~0u, s0, o);
        const float m0 = s0 * (1.f / D_MODEL);
        float q0 = 0.f;
#pragma unroll
        for (int i = 0; i < 8; i++) {
            float d;
            d = bf_lo(a[i]) - m0; q0 += d * d; d = bf_hi(a[i]) - m0; q0 += d * d;
        }
#pragma unroll
        for (int o = 16; o > 0; o >>= 1) q0 += __shfl_xor_sync(~0u, q0, o);
        const float mean = bf16r(m0);
        const float var = bf16r(q0 * (1.f / D_MODEL));
        const float den = bf16r(sqrtf(bf16r(var + 1e-5f)));
        const float rden = 1.f / den;
        uint32_t o[8];
#pragma unroll
        for (int i = 0; i < 8; i++) o[i] = pack_bf16(bf16r(bf_lo(a[i]) - mean) * rden, bf16r(bf_hi(a[i]) - mean) * rden);
        const uint32_t dst = sb + SM_XN + u * 1024 + lane * 32;
        sts_u4(dst, o[0], o[1], o[2], o[3]);
        sts_u4(dst + 16, o[4], o[5], o[6], o[7]);
        TS(0);
    }

    const int lrow = (lane & 7) + ((lane >> 4) << 3);
    const int lchk = (lane >> 3) & 1;

    bar_sync(1, NTHREADS);
    const uint32_t tag = lds_u1(sb + SM_EPOCH);

    auto gemv512 = [&](const int ch0, const uint32_t vaddr, const bool release) {
        float acc[4] = {};
        const uint32_t xa = vaddr + ((u >> 2) * 16 + ft) * 4;
        const int row = (u >> 2) * 32 + lrow;
        const uint32_t wa = sb + row * 128 + ((((u & 3) * 2 + lchk) ^ (row & 7)) << 4);
#pragma unroll
        for (int q = 0; q < 8; q++) {
            const uint32_t b0 = lds_u1(xa + q * 128), b1 = lds_u1(xa + q * 128 + 16), b2 = lds_u1(xa + q * 128 + 32),
                           b3 = lds_u1(xa + q * 128 + 48);
            mbar_wait(bars + (ch0 + q) * 8);
            uint32_t a0[4], a1[4];
            ldsm4t(a0, wa + slot_off(ch0 + q));
            ldsm4t(a1, wa + slot_off(ch0 + q) + 2048);
            mma16816(acc, a0[0], a0[1], a0[2], a0[3], b0, b1);
            mma16816(acc, a1[0], a1[1], a1[2], a1[3], b2, b3);
            if (release && lane == 0) mbar_arrive(bars + (BAR_EMPTY + ch0 + q) * 8);
        }
        if (ft == 0) {
            sts_f1(sb + SM_REDA + ((u >> 2) * 64 + (u & 3) * 16 + fg) * 4, acc[0]);
            sts_f1(sb + SM_REDA + ((u >> 2) * 64 + (u & 3) * 16 + fg + 8) * 4, acc[2]);
        }
    };

    gemv512(CH_WQ, sb + SM_XN + (bh >> 3) * 1024, true);
    TS(1);
    asm volatile("barrier.cluster.wait.acquire.aligned;" ::: "memory");
    bar_sync(2, NCT);
    if (u == 0) {
        const float2 s0 = lds_f2(sb + SM_REDA + lane * 8), s1 = lds_f2(sb + SM_REDA + 256 + lane * 8);
        const uint32_t qp = pack_bf16(s0.x + s1.x, s0.y + s1.y);
        const uint32_t dst = sb + SM_Q + (((j >> 1) * 4 + (lane & 3)) * 16 + (j & 1) * 8 + (lane >> 2)) * 4;
#pragma unroll
        for (int k = 0; k < 8; k++)
            asm volatile("st.async.weak.shared::cluster.mbarrier::complete_tx::bytes.u32 [%0], %1, [%2];"
                         ::"r"(mapa(dst, k)), "r"(qp), "r"(mapa(bars + BAR_Q * 8, k)) : "memory");
        TS(2);
    }

    if (c < 112) {
        uint32_t xb[4][2];
#pragma unroll
        for (int q = 0; q < 4; q++) {
            xb[q][0] = lds_u1(sb + SM_XN + (fg & 1) * 1024 + (q * 64 + u * 8 + ft) * 4);
            xb[q][1] = lds_u1(sb + SM_XN + (fg & 1) * 1024 + (q * 64 + u * 8 + 4 + ft) * 4);
        }
        float acc[4] = {};
#pragma unroll
        for (int q = 0; q < 4; q++) {
            if ((q & 1) == 0) mbar_wait(bars + (CH_W1 + (q >> 1)) * 8);
            const int row = (q & 1) * 128 + u * 16 + lrow;
            uint32_t a[4];
            ldsm4t(a, sb + slot_off(CH_W1 + (q >> 1)) + row * 32 + ((lchk ^ ((row >> 2) & 1)) << 4));
            mma16816(acc, a[0], a[1], a[2], a[3], xb[q][0], xb[q][1]);
            if ((q & 1) && lane == 0) mbar_arrive(bars + (BAR_EMPTY + CH_W1 + (q >> 1)) * 8);
        }
        TS(10);
        if (ft == 0) {
            const uint32_t rb = sb + SM_REDB + u * 128;
            sts_f1(rb + fg * 4, acc[0]);
            sts_f1(rb + 64 + fg * 4, acc[1]);
            sts_f1(rb + (fg + 8) * 4, acc[2]);
            sts_f1(rb + 64 + (fg + 8) * 4, acc[3]);
        }
        bar_sync(2, NCT);
        if (u == 1 && lane < 16) {
            float2 s = make_float2(0.f, 0.f);
#pragma unroll
            for (int k = 0; k < NCW; k++) {
                float2 v = lds_f2(sb + SM_REDB + k * 128 + lane * 8);
                s.x += v.x; s.y += v.y;
            }
            float h[2] = {bf16r(bf16r(s.x) + bf_lo(b1pair)), bf16r(bf16r(s.y) + bf_hi(b1pair))};
            float a[2];
#pragma unroll
            for (int i = 0; i < 2; i++) {
                const float e = bf16r(__expf(-fabsf(h[i])));
                const float sp = bf16r(bf16r(log1pf(e)) + fmaxf(h[i], 0.f));
                a[i] = h[i] * bf16r(tanhf(sp));
            }
            const int dp = lane & 7;
            st_ll1(&sc->ax[(((lane >> 3) * 112 + c) * 4 + (dp & 3)) * 2 + (dp >> 2)], pack_bf16(a[0], a[1]), tag);
            TS(7);
        }
    } else if (lane == 0) {
        mbar_arrive(bars + (BAR_EMPTY + CH_W1) * 8);
        mbar_arrive(bars + (BAR_EMPTY + CH_W1 + 1) * 8);
    }
    __syncwarp();

    {
        mbar_wait_cluster(bars + BAR_Q * 8);
        TS(3);
        uint32_t qa[16];
#pragma unroll
        for (int i = 0; i < 4; i++) lds_u4(qa + 4 * i, sb + SM_Q + ((fg & 3) * 4 + ft) * 64 + i * 16);
        mbar_wait(bars + (CH_K + u) * 8);
        TS(4);
        float acc[4][4] = {};
        const uint32_t kb = sb + ((CH_K + u) % NSLOT) * 8192 + (lane & 7) * 128;
#pragma unroll
        for (int q = 0; q < 4; q++) {
            const int chunk = q * 4 + (lane >> 3);
            const uint32_t off = (chunk >> 3) * 4096 + (((chunk & 7) ^ (lane & 7)) << 4);
#pragma unroll
            for (int nt = 0; nt < 4; nt++) {
                uint32_t b[4];
                ldsm4(b, kb + nt * 1024 + off);
                mma16816(acc[nt], qa[4 * q], 0u, qa[4 * q + 1], 0u, b[0], b[1]);
                mma16816(acc[nt], qa[4 * q + 2], 0u, qa[4 * q + 3], 0u, b[2], b[3]);
            }
        }
        if (lane == 0) mbar_arrive(bars + (BAR_EMPTY + CH_K + u) * 8);
        const float scale = 0.08838834764831845f;
        float sv[8];
#pragma unroll
        for (int i = 0; i < 8; i++) sv[i] = bf16r(bf16r(acc[i >> 1][i & 1]) * scale);
        float m = fmaxf(fmaxf(fmaxf(sv[0], sv[1]), fmaxf(sv[2], sv[3])), fmaxf(fmaxf(sv[4], sv[5]), fmaxf(sv[6], sv[7])));
        m = fmaxf(m, __shfl_xor_sync(~0u, m, 1));
        m = fmaxf(m, __shfl_xor_sync(~0u, m, 2));
        if (lane < 16 && ft == 0) sts_f1(sb + SM_MAX + (u * 4 + fg) * 4, m);
        TS(5);
        bar_sync(2, NCT);
        m = lds_f1(sb + SM_MAX + ((ft + 4 * (fg >> 2)) * 4 + (fg & 3)) * 4);
        m = fmaxf(m, __shfl_xor_sync(~0u, m, 1));
        m = fmaxf(m, __shfl_xor_sync(~0u, m, 2));
        m = fmaxf(m, __shfl_xor_sync(~0u, m, 16));
#pragma unroll
        for (int i = 0; i < 8; i++) sv[i] = ex2((sv[i] - m) * LOG2E);
        float l = ((sv[0] + sv[1]) + (sv[2] + sv[3])) + ((sv[4] + sv[5]) + (sv[6] + sv[7]));
        l += __shfl_xor_sync(~0u, l, 1);
        l += __shfl_xor_sync(~0u, l, 2);
        if (lane < 16) {
            sts_u4(sb + SM_P + (u * 16 + lane) * 16, pack_bf16(sv[0], sv[1]), pack_bf16(sv[2], sv[3]), pack_bf16(sv[4], sv[5]),
                   pack_bf16(sv[6], sv[7]));
            if (ft == 0) sts_f1(sb + SM_SUM + (u * 4 + fg) * 4, l);
        }
        bar_sync(4, NCT + 32);
        TS(6);
    }

    unsigned long long w[2][2] = {};
    const unsigned long long* sa = &sc->ax[(((fg & 1) * 112 + r * 14 + (u < 7 ? u : 0)) * 4 + ft) * 2];
    if (lane < 8) {
        ld_ll2(sa, w[0][0], w[0][1]);
        ld_ll2(sa + 56, w[1][0], w[1][1]);
    }
    {
        float acc[2][4] = {};
        const uint32_t voff = (u >> 2) * 4096 + lane * 128;
        const uint32_t c0 = (((u & 3) * 2) ^ (lane & 7)) << 4, c1 = (((u & 3) * 2 + 1) ^ (lane & 7)) << 4;
#pragma unroll
        for (int i = 0; i < 8; i++) {
            uint32_t pa[4], b0[4], b1[4];
            lds_u4(pa, sb + SM_P + (i * 16 + (lane & 15)) * 16);
            mbar_wait(bars + (CH_V + i) * 8);
            ldsm4t(b0, sb + slot_off(CH_V + i) + voff + c0);
            ldsm4t(b1, sb + slot_off(CH_V + i) + voff + c1);
            mma16816(acc[0], pa[0], 0u, pa[1], 0u, b0[0], b0[1]);
            mma16816(acc[1], pa[0], 0u, pa[1], 0u, b1[0], b1[1]);
            mma16816(acc[0], pa[2], 0u, pa[3], 0u, b0[2], b0[3]);
            mma16816(acc[1], pa[2], 0u, pa[3], 0u, b1[2], b1[3]);
            if (CH_V + i < NEMPTY && lane == 0) mbar_arrive(bars + (BAR_EMPTY + CH_V + i) * 8);
        }
        TS(8);
        if (lane < 16) {
            const uint32_t dst = mapa(sb + SM_INB + j * 256 + lane * 16, u);
            const uint32_t rbar = mapa(bars + BAR_PO * 8, u);
            asm volatile("st.async.weak.shared::cluster.mbarrier::complete_tx::bytes.v4.f32 [%0], {%1, %2, %3, %4}, [%5];"
                         ::"r"(dst), "f"(acc[0][0]), "f"(acc[0][1]), "f"(acc[1][0]), "f"(acc[1][1]), "r"(rbar) : "memory");
        }
        TS(9);
    }

    {
        if (lane < 8) {
            unsigned n = 0;
            while (!(tag_ok(w[0][0], w[0][1], tag) && tag_ok(w[1][0], w[1][1], tag)) && ++n < SPIN_LIMIT) {
                ld_ll2(sa, w[0][0], w[0][1]);
                ld_ll2(sa + 56, w[1][0], w[1][1]);
            }
        }
        __syncwarp();
        if (u < 7) {
            float acc[2][4] = {};
#pragma unroll
            for (int q = 0; q < 2; q++) {
                mbar_wait(bars + (CH_W2 + q) * 8);
                gemv_tile64(acc, sb + slot_off(CH_W2 + q), u * 16 + lrow, lchk, (uint32_t)w[q][0], (uint32_t)w[q][1]);
            }
            if (ft == 0) {
                const uint32_t rb = sb + SM_REDG + u * 256;
#pragma unroll
                for (int mt = 0; mt < 2; mt++) {
                    sts_f1(rb + (mt * 16 + fg) * 4, acc[mt][0]);
                    sts_f1(rb + 128 + (mt * 16 + fg) * 4, acc[mt][1]);
                    sts_f1(rb + (mt * 16 + fg + 8) * 4, acc[mt][2]);
                    sts_f1(rb + 128 + (mt * 16 + fg + 8) * 4, acc[mt][3]);
                }
            }
            bar_arrive(3, NCT);
        } else {
            bar_sync(3, NCT);
            float2 s = make_float2(0.f, 0.f);
#pragma unroll
            for (int k = 0; k < 7; k++) {
                const float2 t = lds_f2(sb + SM_REDG + k * 256 + lane * 8);
                s.x += t.x; s.y += t.y;
            }
            st_ll2(&sc->pf[(g16 * 8 + r) * 64 + lane * 2], __float_as_uint(s.x), __float_as_uint(s.y), tag);
        }
        TS(11);
    }

    mbar_wait_cluster(bars + BAR_O * 8);
    TS(12);
    gemv512(CH_WO, sb + SM_O, false);
    TS(14);
    if (u != 0) { bar_arrive(2, NCT); return; }
    bar_sync(2, NCT);
    {
        const float2 s0 = lds_f2(sb + SM_REDA + lane * 8), s1 = lds_f2(sb + SM_REDA + 256 + lane * 8);
        float2 s = make_float2(s0.x + s1.x, s0.y + s1.y);
        unsigned long long* pa = &sc->pa[(((bh >> 3) * 8 + j) * 8) * 64 + lane * 2];
        if ((bh & 7) != 0) {
            st_ll2(pa + (bh & 7) * 64, __float_as_uint(s.x), __float_as_uint(s.y), tag);
            TS(15);
            return;
        }
        TS(15);
        const unsigned long long* pf = &sc->pf[((2 * j + (lane >> 4)) * 8) * 64 + (bh >> 3) * 32 + (lane & 15) * 2];
        unsigned long long v[15][2] = {};
        unsigned n = 0;
        while (true) {
#pragma unroll
            for (int i = 0; i < 15; i++)
                if (!tag_ok(v[i][0], v[i][1], tag)) ld_ll2(i < 7 ? pa + (i + 1) * 64 : pf + (i - 7) * 64, v[i][0], v[i][1]);
            bool ok = true;
#pragma unroll
            for (int i = 0; i < 15; i++) ok = ok && tag_ok(v[i][0], v[i][1], tag);
            if (ok || ++n >= SPIN_LIMIT) break;
        }
#pragma unroll
        for (int i = 0; i < 15; i++) { s.x += __uint_as_float((uint32_t)v[i][0]); s.y += __uint_as_float((uint32_t)v[i][1]); }
        reinterpret_cast<uint32_t*>(p.out)[(bh >> 3) * 256 + j * 32 + lane] = pack_bf16(bf_lo(xres) + s.x, bf_hi(xres) + s.y);
        __syncwarp();
        if (c == 0 && lane == 0) sc->epoch = tag;
        TS(16);
    }
}

typedef CUresult (*EncodeTiledFn)(CUtensorMap*, CUtensorMapDataType, cuuint32_t, void*, const cuuint64_t*, const cuuint64_t*,
                                  const cuuint32_t*, const cuuint32_t*, CUtensorMapInterleave, CUtensorMapSwizzle,
                                  CUtensorMapL2promotion, CUtensorMapFloatOOBfill);

void make_map(EncodeTiledFn enc, CUtensorMap* m, const void* base, uint64_t cols, uint64_t rows, uint32_t box_c, uint32_t box_r,
              CUtensorMapSwizzle sw) {
    cuuint64_t gd[2] = {cols, rows};
    cuuint64_t gs[1] = {cols * 2};
    cuuint32_t bd[2] = {box_c, box_r};
    cuuint32_t es[2] = {1, 1};
    enc(m, CU_TENSOR_MAP_DATA_TYPE_BFLOAT16, 2, const_cast<void*>(base), gd, gs, bd, es, CU_TENSOR_MAP_INTERLEAVE_NONE, sw,
        CU_TENSOR_MAP_L2_PROMOTION_L2_128B, CU_TENSOR_MAP_FLOAT_OOB_FILL_NONE);
}

}

extern "C" void kernel_launch(void* const* d_in, const int* in_sizes, int n_in, void* d_out, int out_size) {
    (void)in_sizes; (void)n_in; (void)out_size;
    static EncodeTiledFn enc = nullptr;
    static Scratch* sc = nullptr;
    if (!enc) {
        void* fn = nullptr;
        cudaDriverEntryPointQueryResult st;
        cudaGetDriverEntryPoint("cuTensorMapEncodeTiled", &fn, cudaEnableDefault, &st);
        enc = (EncodeTiledFn)fn;
        cudaFuncSetAttribute(fused_decode_kernel, cudaFuncAttributeMaxDynamicSharedMemorySize, SM_TOTAL);
        void* sp = nullptr;
        cudaGetSymbolAddress(&sp, g_scratch);
        sc = (Scratch*)sp;
    }
    Params p;
    make_map(enc, &p.k, d_in[1], 128, 2 * 8 * SK, 64, 32, CU_TENSOR_MAP_SWIZZLE_128B);
    make_map(enc, &p.v, d_in[2], 128, 2 * 8 * SK, 64, 32, CU_TENSOR_MAP_SWIZZLE_128B);
    make_map(enc, &p.wq, d_in[3], 4096, 512, 64, 64, CU_TENSOR_MAP_SWIZZLE_128B);
    make_map(enc, &p.wo, d_in[4], 512, 4096, 64, 64, CU_TENSOR_MAP_SWIZZLE_128B);
    make_map(enc, &p.w1, d_in[6], FF, 512, 16, 256, CU_TENSOR_MAP_SWIZZLE_32B);
    make_map(enc, &p.w2, d_in[8], 512, FF, 32, 112, CU_TENSOR_MAP_SWIZZLE_64B);
    p.x = (const __nv_bfloat16*)d_in[0];
    p.b1 = (const __nv_bfloat16*)d_in[7];
    p.out = (__nv_bfloat16*)d_out;
    p.sc = sc;
    fused_decode_kernel<<<NCTA, NTHREADS, SM_TOTAL, cudaStreamPerThread>>>(p);
}
```

```cpp
#include <cuda_runtime.h>
#include <cuda_bf16.h>
#include <cuda.h>
#include <stdint.h>

namespace {

constexpr int D_MODEL = 512;
constexpr int SK = 8192;
constexpr int WIN = 2048;
constexpr int WIN0 = SK - WIN;
constexpr int FF = 1792;

constexpr int NCTA = 128;
constexpr int NCW = 8;
constexpr int NCT = NCW * 32;
constexpr int NTHREADS = (NCW + 2) * 32;

constexpr int CH_WQ = 0, CH_W1 = 8, CH_K = 10, CH_V = 18, CH_W2 = 26, CH_WO = 28, NCHUNK = 36;
constexpr int NSLOT = 13;
constexpr int NEMPTY = NCHUNK - NSLOT;
#define WINDOW 8
#define WINDOW2 4
__host__ __device__ constexpr int slot_off(int chunk) { return (chunk % NSLOT) * 8192; }

constexpr int BAR_FULL = 0;
constexpr int BAR_EMPTY = NCHUNK;
constexpr int BAR_Q = BAR_EMPTY + NEMPTY;
constexpr int BAR_ST = BAR_Q + 1;
constexpr int BAR_PO = BAR_ST + 1;
constexpr int BAR_O = BAR_PO + 1;
constexpr int NBAR = BAR_O + 1;

constexpr int SM_RING = 0;
constexpr int SM_INB = NSLOT * 8192;
constexpr int SM_INS = SM_INB + 2048;
constexpr int SM_REDA = SM_INS + 256;
constexpr int SM_REDG = SM_REDA + 512;
constexpr int SM_REDB = SM_REDA + 2048;
constexpr int SM_XN = SM_REDB + 1024;
constexpr int SM_P = SM_XN;
constexpr int SM_Q = SM_XN + 2048;
constexpr int SM_O = SM_Q;
constexpr int SM_MAX = SM_Q + 1024;
constexpr int SM_SUM = SM_MAX + 128;
constexpr int SM_BAR = SM_SUM + 128;
constexpr int SM_EPOCH = SM_BAR + NBAR * 8;
constexpr int SM_TOTAL = SM_EPOCH + 8;
static_assert(SM_TOTAL <= 115712, "two CTAs must fit on one SM");

constexpr unsigned SPIN_LIMIT = 1u << 22;

struct Scratch {
    unsigned epoch;
    unsigned pad[31];
    unsigned long long ax[2 * 112 * 8];
    unsigned long long pf[16 * 8 * 64];
    unsigned long long pa[16 * 8 * 64];
};

__device__ Scratch g_scratch;

struct Params {
    CUtensorMap wq, k, v, w1, wo, w2;
    const __nv_bfloat16* x;
    const __nv_bfloat16* b1;
    __nv_bfloat16* out;
    Scratch* sc;
};

__device__ __forceinline__ uint32_t smem_u32(const void* p) { return (uint32_t)__cvta_generic_to_shared(p); }
__device__ __forceinline__ void mbar_init(uint32_t bar, uint32_t cnt) {
    asm volatile("mbarrier.init.shared::cta.b64 [%0], %1;" ::"r"(bar), "r"(cnt) : "memory");
}
__device__ __forceinline__ void mbar_expect_tx(uint32_t bar, uint32_t bytes) {
    asm volatile("mbarrier.arrive.expect_tx.shared::cta.b64 _, [%0], %1;" ::"r"(bar), "r"(bytes) : "memory");
}
__device__ __forceinline__ void mbar_arrive(uint32_t bar) {
    asm volatile("mbarrier.arrive.shared::cta.b64 _, [%0];" ::"r"(bar) : "memory");
}
__device__ __forceinline__ void mbar_wait(uint32_t bar) {
    unsigned n = 0;
    uint32_t ok;
    do {
        asm volatile("{\n.reg .pred p;\nmbarrier.try_wait.parity.shared::cta.b64 p, [%1], 0;\nselp.u32 %0, 1, 0, p;\n}"
                     : "=r"(ok) : "r"(bar) : "memory");
    } while (!ok && ++n < SPIN_LIMIT);
}
__device__ __forceinline__ void mbar_wait_cluster(uint32_t bar) {
    unsigned n = 0;
    uint32_t ok;
    do {
        asm volatile("{\n.reg .pred p;\nmbarrier.try_wait.parity.acquire.cluster.shared::cta.b64 p, [%1], 0;\nselp.u32 %0, 1, 0, p;\n}"
                     : "=r"(ok) : "r"(bar) : "memory");
    } while (!ok && ++n < SPIN_LIMIT);
}
__device__ __forceinline__ void tma2d(uint32_t dst, const CUtensorMap* tm, int c0, int c1, uint32_t bar) {
    asm volatile("cp.async.bulk.tensor.2d.shared::cluster.global.mbarrier::complete_tx::bytes [%0], [%1, {%3, %4}], [%2];"
                 ::"r"(dst), "l"((uint64_t)tm), "r"(bar), "r"(c0), "r"(c1) : "memory");
}
__device__ __forceinline__ uint32_t mapa(uint32_t addr, uint32_t rank) {
    uint32_t r;
    asm("mapa.shared::cluster.u32 %0, %1, %2;" : "=r"(r) : "r"(addr), "r"(rank));
    return r;
}
__device__ __forceinline__ void bar_sync(int id, int n) { asm volatile("bar.sync %0, %1;" ::"r"(id), "r"(n) : "memory"); }
__device__ __forceinline__ void bar_arrive(int id, int n) { asm volatile("bar.arrive %0, %1;" ::"r"(id), "r"(n) : "memory"); }

__device__ __forceinline__ void ldsm4(uint32_t (&r)[4], uint32_t addr) {
    asm volatile("ldmatrix.sync.aligned.m8n8.x4.shared.b16 {%0,%1,%2,%3}, [%4];"
                 : "=r"(r[0]), "=r"(r[1]), "=r"(r[2]), "=r"(r[3]) : "r"(addr) : "memory");
}
__device__ __forceinline__ void ldsm4t(uint32_t (&r)[4], uint32_t addr) {
    asm volatile("ldmatrix.sync.aligned.m8n8.x4.trans.shared.b16 {%0,%1,%2,%3}, [%4];"
                 : "=r"(r[0]), "=r"(r[1]), "=r"(r[2]), "=r"(r[3]) : "r"(addr) : "memory");
}
__device__ __forceinline__ void mma16816(float (&c)[4], uint32_t a0, uint32_t a1, uint32_t a2, uint32_t a3, uint32_t b0, uint32_t b1) {
    asm volatile("mma.sync.aligned.m16n8k16.row.col.f32.bf16.bf16.f32 {%0,%1,%2,%3}, {%4,%5,%6,%7}, {%8,%9}, {%0,%1,%2,%3};"
                 : "+f"(c[0]), "+f"(c[1]), "+f"(c[2]), "+f"(c[3])
                 : "r"(a0), "r"(a1), "r"(a2), "r"(a3), "r"(b0), "r"(b1));
}
__device__ __forceinline__ void st_ll1(unsigned long long* p, uint32_t d, uint32_t tag) {
    unsigned long long w = ((unsigned long long)tag << 32) | d;
    asm volatile("st.relaxed.gpu.global.b64 [%0], %1;" ::"l"(p), "l"(w) : "memory");
}
__device__ __forceinline__ void st_ll2(unsigned long long* p, uint32_t d0, uint32_t d1, uint32_t tag) {
    unsigned long long w0 = ((unsigned long long)tag << 32) | d0, w1 = ((unsigned long long)tag << 32) | d1;
    asm volatile("st.relaxed.gpu.global.v2.b64 [%0], {%1, %2};" ::"l"(p), "l"(w0), "l"(w1) : "memory");
}
__device__ __forceinline__ void ld_ll2(const unsigned long long* p, unsigned long long& w0, unsigned long long& w1) {
    asm volatile("ld.relaxed.gpu.global.v2.b64 {%0, %1}, [%2];" : "=l"(w0), "=l"(w1) : "l"(p) : "memory");
}
__device__ __forceinline__ bool tag_ok(unsigned long long w0, unsigned long long w1, uint32_t tag) {
    return (uint32_t)(w0 >> 32) == tag && (uint32_t)(w1 >> 32) == tag;
}
__device__ __forceinline__ float ex2(float x) {
    float y;
    asm("ex2.approx.ftz.f32 %0, %1;" : "=f"(y) : "f"(x));
    return y;
}
__device__ __forceinline__ float bf16r(float x) { return __bfloat162float(__float2bfloat16_rn(x)); }
__device__ __forceinline__ uint32_t pack_bf16(float lo, float hi) {
    __nv_bfloat162 v = __floats2bfloat162_rn(lo, hi);
    return *reinterpret_cast<uint32_t*>(&v);
}
__device__ __forceinline__ float bf_lo(uint32_t u) { return __uint_as_float(u << 16); }
__device__ __forceinline__ float bf_hi(uint32_t u) { return __uint_as_float(u & 0xffff0000u); }
__device__ __forceinline__ float2 lds_f2(uint32_t a) {
    float2 v;
    asm volatile("ld.shared.v2.f32 {%0, %1}, [%2];" : "=f"(v.x), "=f"(v.y) : "r"(a) : "memory");
    return v;
}
__device__ __forceinline__ float lds_f1(uint32_t a) {
    float v;
    asm volatile("ld.shared.f32 %0, [%1];" : "=f"(v) : "r"(a) : "memory");
    return v;
}
__device__ __forceinline__ uint32_t lds_u1(uint32_t a) {
    uint32_t v;
    asm volatile("ld.shared.u32 %0, [%1];" : "=r"(v) : "r"(a) : "memory");
    return v;
}
__device__ __forceinline__ void lds_u4(uint32_t* r, uint32_t a) {
    asm volatile("ld.shared.v4.u32 {%0,%1,%2,%3}, [%4];" : "=r"(r[0]), "=r"(r[1]), "=r"(r[2]), "=r"(r[3]) : "r"(a) : "memory");
}
__device__ __forceinline__ float4 lds_f4(uint32_t a) {
    float4 v;
    asm volatile("ld.shared.v4.f32 {%0,%1,%2,%3}, [%4];" : "=f"(v.x), "=f"(v.y), "=f"(v.z), "=f"(v.w) : "r"(a) : "memory");
    return v;
}
__device__ __forceinline__ void sts_f2(uint32_t a, float x, float y) {
    asm volatile("st.shared.v2.f32 [%0], {%1, %2};" ::"r"(a), "f"(x), "f"(y) : "memory");
}
__device__ __forceinline__ void sts_f4(uint32_t a, float x, float y, float z, float w) {
    asm volatile("st.shared.v4.f32 [%0], {%1,%2,%3,%4};" ::"r"(a), "f"(x), "f"(y), "f"(z), "f"(w) : "memory");
}
__device__ __forceinline__ void sts_f1(uint32_t a, float v) { asm volatile("st.shared.f32 [%0], %1;" ::"r"(a), "f"(v) : "memory"); }
__device__ __forceinline__ void sts_u1(uint32_t a, uint32_t v) { asm volatile("st.shared.u32 [%0], %1;" ::"r"(a), "r"(v) : "memory"); }
__device__ __forceinline__ void sts_u4(uint32_t a, uint32_t x, uint32_t y, uint32_t z, uint32_t w) {
    asm volatile("st.shared.v4.u32 [%0], {%1,%2,%3,%4};" ::"r"(a), "r"(x), "r"(y), "r"(z), "r"(w) : "memory");
}

#define TS(i) do { } while (0)

__device__ __forceinline__ void gemv_tile64(float (&acc)[2][4], uint32_t base, int row, int lchk, uint32_t b0, uint32_t b1) {
    uint32_t a0[4], a1[4];
    const uint32_t ra = base + row * 64;
    const int sw = (row >> 1) & 3;
    ldsm4t(a0, ra + ((lchk ^ sw) << 4));
    ldsm4t(a1, ra + (((2 + lchk) ^ sw) << 4));
    mma16816(acc[0], a0[0], a0[1], a0[2], a0[3], b0, b1);
    mma16816(acc[1], a1[0], a1[1], a1[2], a1[3], b0, b1);
}

__global__ void __cluster_dims__(8, 1, 1) __launch_bounds__(NTHREADS, 2) fused_decode_kernel(const __grid_constant__ Params p) {
    extern __shared__ __align__(1024) uint8_t smem[];
    const uint32_t sb = smem_u32(smem);
    const uint32_t bars = sb + SM_BAR;
    const int c = blockIdx.x;
    const int warp = threadIdx.x >> 5, lane = threadIdx.x & 31;
    const int bh = c >> 3, j = c & 7;
    const int r = c >> 4, g16 = c & 15;

    if (warp == NCW) {
        const int krow = bh * SK + WIN0 + j * 256;
        if (lane == 0) {
#pragma unroll
            for (int i = 0; i < CH_W1; i++) mbar_init(bars + i * 8, 1);
            asm volatile("fence.proxy.async.shared::cta;" ::: "memory");
#pragma unroll
            for (int i = 0; i < CH_W1; i++) {
                mbar_expect_tx(bars + i * 8, 8192);
                tma2d(sb + slot_off(i), &p.wq, (bh & 7) * 512 + 64 * j, 64 * i, bars + i * 8);
            }
#pragma unroll
            for (int k = CH_W1; k < NCHUNK; k++) mbar_init(bars + k * 8, 1);
            asm volatile("fence.proxy.async.shared::cta;" ::: "memory");
        }
        __syncwarp();
        asm volatile("barrier.cluster.arrive.relaxed.aligned;" ::: "memory");
        bar_sync(1, NTHREADS);
        if (lane == 0) {
#pragma unroll
            for (int i = CH_W1; i < NCHUNK; i++) {
                const uint32_t bar = bars + i * 8;
                const uint32_t dst = sb + slot_off(i);
                if (i >= CH_W2 && i - WINDOW2 < CH_W2) mbar_wait(bar - WINDOW2 * 8);
                else if (i >= WINDOW) mbar_wait(bar - WINDOW * 8);
                if (i >= NSLOT) mbar_wait(bars + (BAR_EMPTY + i - NSLOT) * 8);
                if (i < CH_K) {
                    const int q = i - CH_W1;
                    if (c < 112) {
                        mbar_expect_tx(bar, 8192);
                        tma2d(dst, &p.w1, 16 * c, 256 * q, bar);
                    } else {
                        mbar_expect_tx(bar, 0);
                    }
                } else if (i < CH_V) {
                    const int q = i - CH_K;
                    mbar_expect_tx(bar, 8192);
                    tma2d(dst, &p.k, 0, krow + q * 32, bar);
                    tma2d(dst + 4096, &p.k, 64, krow + q * 32, bar);
                } else if (i < CH_W2) {
                    const int q = i - CH_V;
                    mbar_expect_tx(bar, 8192);
                    tma2d(dst, &p.v, 0, krow + q * 32, bar);
                    tma2d(dst + 4096, &p.v, 64, krow + q * 32, bar);
                } else if (i < CH_WO) {
                    const int q = i - CH_W2;
                    mbar_expect_tx(bar, 7168);
                    tma2d(dst, &p.w2, 32 * g16, 224 * r + 112 * q, bar);
                } else {
                    const int q = i - CH_WO;
                    mbar_expect_tx(bar, 8192);
                    tma2d(dst, &p.wo, 64 * j, 512 * (bh & 7) + 64 * q, bar);
                }
            }
        }
        return;
    }

    Scratch* const sc = p.sc;
    const float LOG2E = 1.4426950408889634f;

    if (warp == NCW + 1) {
        const uint32_t tag = *reinterpret_cast<volatile unsigned*>(&sc->epoch) + 1u;
        const uint32_t xres = __ldg(reinterpret_cast<const uint32_t*>(p.x) + (bh >> 3) * 256 + j * 32 + lane);
        if (lane == 0) {
            mbar_init(bars + BAR_Q * 8, 1);
            mbar_init(bars + BAR_ST * 8, 1);
            mbar_init(bars + BAR_PO * 8, 1);
            mbar_init(bars + BAR_O * 8, 1);
            asm volatile("fence.mbarrier_init.release.cluster;" ::: "memory");
            mbar_expect_tx(bars + BAR_Q * 8, 1024);
            mbar_expect_tx(bars + BAR_ST * 8, 256);
            mbar_expect_tx(bars + BAR_PO * 8, 2048);
            mbar_expect_tx(bars + BAR_O * 8, 1024);
#pragma unroll
            for (int k = 0; k < NEMPTY; k++) mbar_init(bars + (BAR_EMPTY + k) * 8, (k >= CH_K && k < CH_V) ? 1 : NCW);
        }
        __syncwarp();
        asm volatile("barrier.cluster.arrive.relaxed.aligned;" ::: "memory");
        if (lane == 0) sts_u1(sb + SM_EPOCH, tag);
        __syncwarp();
        bar_arrive(1, NTHREADS);
        TS(0);
        asm volatile("barrier.cluster.wait.acquire.aligned;" ::: "memory");
        bar_sync(4, NCT + 32);
        {
            float mx = lds_f1(sb + SM_MAX + lane * 4);
            float sm = lds_f1(sb + SM_SUM + lane * 4);
#pragma unroll
            for (int o = 4; o < 32; o <<= 1) { mx = fmaxf(mx, __shfl_xor_sync(~0u, mx, o)); sm += __shfl_xor_sync(~0u, sm, o); }
            const uint32_t dst = mapa(sb + SM_INS + (j * 4 + (lane & 3)) * 8, lane >> 2);
            const uint32_t rbar = mapa(bars + BAR_ST * 8, lane >> 2);
            asm volatile("st.async.weak.shared::cluster.mbarrier::complete_tx::bytes.v2.f32 [%0], {%1, %2}, [%3];"
                         ::"r"(dst), "f"(mx), "f"(sm), "r"(rbar) : "memory");
        }
        TS(2);
        float coef[8];
        {
            mbar_wait_cluster(bars + BAR_ST * 8);
            const float2 st = lds_f2(sb + SM_INS + lane * 8);
            float gm = st.x;
#pragma unroll
            for (int o = 4; o < 32; o <<= 1) gm = fmaxf(gm, __shfl_xor_sync(~0u, gm, o));
            const float wj = ex2((st.x - gm) * LOG2E);
            float gl = wj * st.y;
#pragma unroll
            for (int o = 4; o < 32; o <<= 1) gl += __shfl_xor_sync(~0u, gl, o);
            const float cj = wj / gl;
#pragma unroll
            for (int k = 0; k < 8; k++) coef[k] = __shfl_sync(~0u, cj, k * 4 + (lane >> 3));
        }
        TS(3);
        mbar_wait_cluster(bars + BAR_PO * 8);
        {
            float o0 = 0.f, o1 = 0.f;
#pragma unroll
            for (int k = 0; k < 8; k++) {
                const float2 v = lds_f2(sb + SM_INB + k * 256 + lane * 8);
                o0 = fmaf(coef[k], v.x, o0);
                o1 = fmaf(coef[k], v.y, o1);
            }
            const uint32_t op = pack_bf16(o0, o1);
            const uint32_t dst = sb + SM_O + ((lane >> 3) * 64 + j * 8 + (lane & 1) * 4 + ((lane >> 1) & 3)) * 4;
#pragma unroll
            for (int k = 0; k < 8; k++)
                asm volatile("st.async.weak.shared::cluster.mbarrier::complete_tx::bytes.u32 [%0], %1, [%2];"
                             ::"r"(mapa(dst, k)), "r"(op), "r"(mapa(bars + BAR_O * 8, k)) : "memory");
        }
        TS(4);
        if ((bh & 7) != 0) return;
        float2 s = make_float2(bf_lo(xres), bf_hi(xres));
#pragma unroll
        for (int part = 0; part < 2; part++) {
            const unsigned long long* src = part == 0 ? &sc->pf[((2 * j + (lane >> 4)) * 8) * 64 + (bh >> 3) * 32 + (lane & 15) * 2]
                                                      : &sc->pa[(((bh >> 3) * 8 + j) * 8) * 64 + lane * 2];
            unsigned long long v[8][2] = {};
            unsigned n = 0;
            while (true) {
#pragma unroll
                for (int i = 0; i < 8; i++)
                    if (!tag_ok(v[i][0], v[i][1], tag)) ld_ll2(src + i * 64, v[i][0], v[i][1]);
                bool ok = true;
#pragma unroll
                for (int i = 0; i < 8; i++) ok = ok && tag_ok(v[i][0], v[i][1], tag);
                if (ok || ++n >= SPIN_LIMIT) break;
            }
#pragma unroll
            for (int i = 0; i < 8; i++) { s.x += __uint_as_float((uint32_t)v[i][0]); s.y += __uint_as_float((uint32_t)v[i][1]); }
        }
        reinterpret_cast<uint32_t*>(p.out)[(bh >> 3) * 256 + j * 32 + lane] = pack_bf16(s.x, s.y);
        __syncwarp();
        if (c == 0 && lane == 0) sc->epoch = tag;
        TS(16);
        return;
    }

    const int u = warp;
    const int fg = lane >> 2, ft = lane & 3;
    asm volatile("barrier.cluster.arrive.relaxed.aligned;" ::: "memory");

    uint32_t b1pair = 0;
    if (u < 2) {
        const uint4* x4 = reinterpret_cast<const uint4*>(p.x) + u * 64 + lane * 2;
        const uint4 v0 = __ldg(x4), v1 = __ldg(x4 + 1);
        if (u == 1 && c < 112) b1pair = __ldg(reinterpret_cast<const uint32_t*>(p.b1) + c * 8 + (lane & 7));
        const uint32_t a[8] = {v0.x, v0.y, v0.z, v0.w, v1.x, v1.y, v1.z, v1.w};
        float s0 = 0.f;
#pragma unroll
        for (int i = 0; i < 8; i++) s0 += bf_lo(a[i]) + bf_hi(a[i]);
#pragma unroll
        for (int o = 16; o > 0; o >>= 1) s0 += __shfl_xor_sync(~0u, s0, o);
        const float m0 = s0 * (1.f / D_MODEL);
        float q0 = 0.f;
#pragma unroll
        for (int i = 0; i < 8; i++) {
            float d;
            d = bf_lo(a[i]) - m0; q0 += d * d; d = bf_hi(a[i]) - m0; q0 += d * d;
        }
#pragma unroll
        for (int o = 16; o > 0; o >>= 1) q0 += __shfl_xor_sync(~0u, q0, o);
        const float mean = bf16r(m0);
        const float var = bf16r(q0 * (1.f / D_MODEL));
        const float den = bf16r(sqrtf(bf16r(var + 1e-5f)));
        const float rden = 1.f / den;
        uint32_t o[8];
#pragma unroll
        for (int i = 0; i < 8; i++) o[i] = pack_bf16(bf16r(bf_lo(a[i]) - mean) * rden, bf16r(bf_hi(a[i]) - mean) * rden);
        const uint32_t dst = sb + SM_XN + u * 1024 + lane * 32;
        sts_u4(dst, o[0], o[1], o[2], o[3]);
        sts_u4(dst + 16, o[4], o[5], o[6], o[7]);
        TS(0);
    }

    const int lrow = (lane & 7) + ((lane >> 4) << 3);
    const int lchk = (lane >> 3) & 1;

    bar_sync(1, NTHREADS);
    const uint32_t tag = lds_u1(sb + SM_EPOCH);

    auto gemv512 = [&](const int ch0, const uint32_t vaddr, const bool release) {
        float acc[4] = {}, acc2[4] = {};
        const uint32_t xa = vaddr + ((u >> 2) * 16 + ft) * 4;
        const int row = (u >> 2) * 32 + lrow;
        const uint32_t wa = sb + row * 128 + ((((u & 3) * 2 + lchk) ^ (row & 7)) << 4);
        uint32_t bb[8][4];
#pragma unroll
        for (int q = 0; q < 8; q++)
#pragma unroll
            for (int i = 0; i < 4; i++) bb[q][i] = lds_u1(xa + q * 128 + i * 16);
#pragma unroll
        for (int q = 0; q < 8; q++) {
            mbar_wait(bars + (ch0 + q) * 8);
            uint32_t a0[4], a1[4];
            ldsm4t(a0, wa + slot_off(ch0 + q));
            ldsm4t(a1, wa + slot_off(ch0 + q) + 2048);
            mma16816(acc, a0[0], a0[1], a0[2], a0[3], bb[q][0], bb[q][1]);
            mma16816(acc2, a1[0], a1[1], a1[2], a1[3], bb[q][2], bb[q][3]);
            if (release && lane == 0) mbar_arrive(bars + (BAR_EMPTY + ch0 + q) * 8);
        }
        acc[0] += acc2[0]; acc[2] += acc2[2];
        if (ft == 0) {
            sts_f1(sb + SM_REDA + ((u >> 2) * 64 + (u & 3) * 16 + fg) * 4, acc[0]);
            sts_f1(sb + SM_REDA + ((u >> 2) * 64 + (u & 3) * 16 + fg + 8) * 4, acc[2]);
        }
    };

    gemv512(CH_WQ, sb + SM_XN + (bh >> 3) * 1024, true);
    TS(1);
    asm volatile("barrier.cluster.wait.acquire.aligned;" ::: "memory");
    bar_sync(2, NCT);
    if (u == 0) {
        const float2 s0 = lds_f2(sb + SM_REDA + lane * 8), s1 = lds_f2(sb + SM_REDA + 256 + lane * 8);
        const uint32_t qp = pack_bf16(s0.x + s1.x, s0.y + s1.y);
        const uint32_t dst = sb + SM_Q + (((j >> 1) * 4 + (lane & 3)) * 16 + (j & 1) * 8 + (lane >> 2)) * 4;
#pragma unroll
        for (int k = 0; k < 8; k++)
            asm volatile("st.async.weak.shared::cluster.mbarrier::complete_tx::bytes.u32 [%0], %1, [%2];"
                         ::"r"(mapa(dst, k)), "r"(qp), "r"(mapa(bars + BAR_Q * 8, k)) : "memory");
        TS(2);
    }

    if (c < 112) {
        uint32_t xb[4][2];
#pragma unroll
        for (int q = 0; q < 4; q++) {
            xb[q][0] = lds_u1(sb + SM_XN + (fg & 1) * 1024 + (q * 64 + u * 8 + ft) * 4);
            xb[q][1] = lds_u1(sb + SM_XN + (fg & 1) * 1024 + (q * 64 + u * 8 + 4 + ft) * 4);
        }
        float acc[4] = {};
#pragma unroll
        for (int q = 0; q < 4; q++) {
            if ((q & 1) == 0) mbar_wait(bars + (CH_W1 + (q >> 1)) * 8);
            const int row = (q & 1) * 128 + u * 16 + lrow;
            uint32_t a[4];
            ldsm4t(a, sb + slot_off(CH_W1 + (q >> 1)) + row * 32 + ((lchk ^ ((row >> 2) & 1)) << 4));
            mma16816(acc, a[0], a[1], a[2], a[3], xb[q][0], xb[q][1]);
            if ((q & 1) && lane == 0) mbar_arrive(bars + (BAR_EMPTY + CH_W1 + (q >> 1)) * 8);
        }
        TS(10);
        if (ft == 0) {
            const uint32_t rb = sb + SM_REDB + u * 128;
            sts_f1(rb + fg * 4, acc[0]);
            sts_f1(rb + 64 + fg * 4, acc[1]);
            sts_f1(rb + (fg + 8) * 4, acc[2]);
            sts_f1(rb + 64 + (fg + 8) * 4, acc[3]);
        }
        bar_sync(2, NCT);
        if (u == 1 && lane < 16) {
            float2 s = make_float2(0.f, 0.f);
#pragma unroll
            for (int k = 0; k < NCW; k++) {
                float2 v = lds_f2(sb + SM_REDB + k * 128 + lane * 8);
                s.x += v.x; s.y += v.y;
            }
            float h[2] = {bf16r(bf16r(s.x) + bf_lo(b1pair)), bf16r(bf16r(s.y) + bf_hi(b1pair))};
            float a[2];
#pragma unroll
            for (int i = 0; i < 2; i++) {
                const float e = bf16r(__expf(-fabsf(h[i])));
                const float sp = bf16r(bf16r(log1pf(e)) + fmaxf(h[i], 0.f));
                a[i] = h[i] * bf16r(tanhf(sp));
            }
            const int dp = lane & 7;
            st_ll1(&sc->ax[(((lane >> 3) * 112 + c) * 4 + (dp & 3)) * 2 + (dp >> 2)], pack_bf16(a[0], a[1]), tag);
            TS(7);
        }
    } else if (lane == 0) {
        mbar_arrive(bars + (BAR_EMPTY + CH_W1) * 8);
        mbar_arrive(bars + (BAR_EMPTY + CH_W1 + 1) * 8);
    }
    __syncwarp();

    {
        mbar_wait_cluster(bars + BAR_Q * 8);
        TS(3);
        uint32_t qa[16];
#pragma unroll
        for (int i = 0; i < 4; i++) lds_u4(qa + 4 * i, sb + SM_Q + ((fg & 3) * 4 + ft) * 64 + i * 16);
        mbar_wait(bars + (CH_K + u) * 8);
        TS(4);
        float acc[4][4] = {};
        const uint32_t kb = sb + ((CH_K + u) % NSLOT) * 8192 + (lane & 7) * 128;
#pragma unroll
        for (int q = 0; q < 4; q++) {
            const int chunk = q * 4 + (lane >> 3);
            const uint32_t off = (chunk >> 3) * 4096 + (((chunk & 7) ^ (lane & 7)) << 4);
#pragma unroll
            for (int nt = 0; nt < 4; nt++) {
                uint32_t b[4];
                ldsm4(b, kb + nt * 1024 + off);
                mma16816(acc[nt], qa[4 * q], 0u, qa[4 * q + 1], 0u, b[0], b[1]);
                mma16816(acc[nt], qa[4 * q + 2], 0u, qa[4 * q + 3], 0u, b[2], b[3]);
            }
        }
        if (lane == 0) mbar_arrive(bars + (BAR_EMPTY + CH_K + u) * 8);
        const float scale = 0.08838834764831845f;
        float sv[8];
#pragma unroll
        for (int i = 0; i < 8; i++) sv[i] = bf16r(bf16r(acc[i >> 1][i & 1]) * scale);
        float m = fmaxf(fmaxf(fmaxf(sv[0], sv[1]), fmaxf(sv[2], sv[3])), fmaxf(fmaxf(sv[4], sv[5]), fmaxf(sv[6], sv[7])));
        m = fmaxf(m, __shfl_xor_sync(~0u, m, 1));
        m = fmaxf(m, __shfl_xor_sync(~0u, m, 2));
        if (lane < 16 && ft == 0) sts_f1(sb + SM_MAX + (u * 4 + fg) * 4, m);
        TS(5);
        bar_sync(2, NCT);
        m = lds_f1(sb + SM_MAX + ((ft + 4 * (fg >> 2)) * 4 + (fg & 3)) * 4);
        m = fmaxf(m, __shfl_xor_sync(~0u, m, 1));
        m = fmaxf(m, __shfl_xor_sync(~0u, m, 2));
        m = fmaxf(m, __shfl_xor_sync(~0u, m, 16));
#pragma unroll
        for (int i = 0; i < 8; i++) sv[i] = ex2((sv[i] - m) * LOG2E);
        float l = ((sv[0] + sv[1]) + (sv[2] + sv[3])) + ((sv[4] + sv[5]) + (sv[6] + sv[7]));
        l += __shfl_xor_sync(~0u, l, 1);
        l += __shfl_xor_sync(~0u, l, 2);
        if (lane < 16) {
            sts_u4(sb + SM_P + (u * 16 + lane) * 16, pack_bf16(sv[0], sv[1]), pack_bf16(sv[2], sv[3]), pack_bf16(sv[4], sv[5]),
                   pack_bf16(sv[6], sv[7]));
            if (ft == 0) sts_f1(sb + SM_SUM + (u * 4 + fg) * 4, l);
        }
        bar_sync(4, NCT + 32);
        TS(6);
    }

    unsigned long long w[2][2] = {};
    const unsigned long long* sa = &sc->ax[(((fg & 1) * 112 + r * 14 + (u < 7 ? u : 0)) * 4 + ft) * 2];
    if (lane < 8) {
        ld_ll2(sa, w[0][0], w[0][1]);
        ld_ll2(sa + 56, w[1][0], w[1][1]);
    }
    {
        float acc[2][4] = {};
        const uint32_t voff = (u >> 2) * 4096 + lane * 128;
        const uint32_t c0 = (((u & 3) * 2) ^ (lane & 7)) << 4, c1 = (((u & 3) * 2 + 1) ^ (lane & 7)) << 4;
#pragma unroll
        for (int i = 0; i < 8; i++) {
            uint32_t pa[4], b0[4], b1[4];
            lds_u4(pa, sb + SM_P + (i * 16 + (lane & 15)) * 16);
            mbar_wait(bars + (CH_V + i) * 8);
            ldsm4t(b0, sb + slot_off(CH_V + i) + voff + c0);
            ldsm4t(b1, sb + slot_off(CH_V + i) + voff + c1);
            mma16816(acc[0], pa[0], 0u, pa[1], 0u, b0[0], b0[1]);
            mma16816(acc[1], pa[0], 0u, pa[1], 0u, b1[0], b1[1]);
            mma16816(acc[0], pa[2], 0u, pa[3], 0u, b0[2], b0[3]);
            mma16816(acc[1], pa[2], 0u, pa[3], 0u, b1[2], b1[3]);
            if (CH_V + i < NEMPTY && lane == 0) mbar_arrive(bars + (BAR_EMPTY + CH_V + i) * 8);
        }
        TS(8);
        if (lane < 16) {
            const uint32_t dst = mapa(sb + SM_INB + j * 256 + lane * 16, u);
            const uint32_t rbar = mapa(bars + BAR_PO * 8, u);
            asm volatile("st.async.weak.shared::cluster.mbarrier::complete_tx::bytes.v4.f32 [%0], {%1, %2, %3, %4}, [%5];"
                         ::"r"(dst), "f"(acc[0][0]), "f"(acc[0][1]), "f"(acc[1][0]), "f"(acc[1][1]), "r"(rbar) : "memory");
        }
        TS(9);
    }

    {
        if (lane < 8) {
            unsigned n = 0;
            while (!(tag_ok(w[0][0], w[0][1], tag) && tag_ok(w[1][0], w[1][1], tag)) && ++n < SPIN_LIMIT) {
                ld_ll2(sa, w[0][0], w[0][1]);
                ld_ll2(sa + 56, w[1][0], w[1][1]);
            }
        }
        __syncwarp();
        if (u < 7) {
            float acc[2][4] = {};
#pragma unroll
            for (int q = 0; q < 2; q++) {
                mbar_wait(bars + (CH_W2 + q) * 8);
                gemv_tile64(acc, sb + slot_off(CH_W2 + q), u * 16 + lrow, lchk, (uint32_t)w[q][0], (uint32_t)w[q][1]);
            }
            if (ft == 0) {
                const uint32_t rb = sb + SM_REDG + u * 256;
#pragma unroll
                for (int mt = 0; mt < 2; mt++) {
                    sts_f1(rb + (mt * 16 + fg) * 4, acc[mt][0]);
                    sts_f1(rb + 128 + (mt * 16 + fg) * 4, acc[mt][1]);
                    sts_f1(rb + (mt * 16 + fg + 8) * 4, acc[mt][2]);
                    sts_f1(rb + 128 + (mt * 16 + fg + 8) * 4, acc[mt][3]);
                }
            }
            bar_arrive(3, NCT);
        } else {
            bar_sync(3, NCT);
            float2 s = make_float2(0.f, 0.f);
#pragma unroll
            for (int k = 0; k < 7; k++) {
                const float2 t = lds_f2(sb + SM_REDG + k * 256 + lane * 8);
                s.x += t.x; s.y += t.y;
            }
            st_ll2(&sc->pf[(g16 * 8 + r) * 64 + lane * 2], __float_as_uint(s.x), __float_as_uint(s.y), tag);
        }
        TS(11);
    }

    mbar_wait_cluster(bars + BAR_O * 8);
    TS(12);
    gemv512(CH_WO, sb + SM_O, false);
    TS(14);
    if (u != 0) { bar_arrive(2, NCT); return; }
    bar_sync(2, NCT);
    {
        const float2 s0 = lds_f2(sb + SM_REDA + lane * 8), s1 = lds_f2(sb + SM_REDA + 256 + lane * 8);
        st_ll2(&sc->pa[((((bh >> 3) * 8 + j) * 8) + (bh & 7)) * 64 + lane * 2], __float_as_uint(s0.x + s1.x),
               __float_as_uint(s0.y + s1.y), tag);
        TS(15);
    }
}

typedef CUresult (*EncodeTiledFn)(CUtensorMap*, CUtensorMapDataType, cuuint32_t, void*, const cuuint64_t*, const cuuint64_t*,
                                  const cuuint32_t*, const cuuint32_t*, CUtensorMapInterleave, CUtensorMapSwizzle,
                                  CUtensorMapL2promotion, CUtensorMapFloatOOBfill);

void make_map(EncodeTiledFn enc, CUtensorMap* m, const void* base, uint64_t cols, uint64_t rows, uint32_t box_c, uint32_t box_r,
              CUtensorMapSwizzle sw) {
    cuuint64_t gd[2] = {cols, rows};
    cuuint64_t gs[1] = {cols * 2};
    cuuint32_t bd[2] = {box_c, box_r};
    cuuint32_t es[2] = {1, 1};
    enc(m, CU_TENSOR_MAP_DATA_TYPE_BFLOAT16, 2, const_cast<void*>(base), gd, gs, bd, es, CU_TENSOR_MAP_INTERLEAVE_NONE, sw,
        CU_TENSOR_MAP_L2_PROMOTION_L2_128B, CU_TENSOR_MAP_FLOAT_OOB_FILL_NONE);
}

}

extern "C" void kernel_launch(void* const* d_in, const int* in_sizes, int n_in, void* d_out, int out_size) {
    (void)in_sizes; (void)n_in; (void)out_size;
    static EncodeTiledFn enc = nullptr;
    static Scratch* sc = nullptr;
    if (!enc) {
        void* fn = nullptr;
        cudaDriverEntryPointQueryResult st;
        cudaGetDriverEntryPoint("cuTensorMapEncodeTiled", &fn, cudaEnableDefault, &st);
        enc = (EncodeTiledFn)fn;
        cudaFuncSetAttribute(fused_decode_kernel, cudaFuncAttributeMaxDynamicSharedMemorySize, SM_TOTAL);
        void* sp = nullptr;
        cudaGetSymbolAddress(&sp, g_scratch);
        sc = (Scratch*)sp;
    }
    Params p;
    make_map(enc, &p.k, d_in[1], 128, 2 * 8 * SK, 64, 32, CU_TENSOR_MAP_SWIZZLE_128B);
    make_map(enc, &p.v, d_in[2], 128, 2 * 8 * SK, 64, 32, CU_TENSOR_MAP_SWIZZLE_128B);
    make_map(enc, &p.wq, d_in[3], 4096, 512, 64, 64, CU_TENSOR_MAP_SWIZZLE_128B);
    make_map(enc, &p.wo, d_in[4], 512, 4096, 64, 64, CU_TENSOR_MAP_SWIZZLE_128B);
    make_map(enc, &p.w1, d_in[6], FF, 512, 16, 256, CU_TENSOR_MAP_SWIZZLE_32B);
    make_map(enc, &p.w2, d_in[8], 512, FF, 32, 112, CU_TENSOR_MAP_SWIZZLE_64B);
    p.x = (const __nv_bfloat16*)d_in[0];
    p.b1 = (const __nv_bfloat16*)d_in[7];
    p.out = (__nv_bfloat16*)d_out;
    p.sc = sc;
    fused_decode_kernel<<<NCTA, NTHREADS, SM_TOTAL, cudaStreamPerThread>>>(p);
}
```

```cpp
#include <cuda_runtime.h>
#include <cuda_bf16.h>
#include <cuda.h>
#include <stdint.h>

namespace {

constexpr int D_MODEL = 512;
constexpr int SK = 8192;
constexpr int WIN = 2048;
constexpr int WIN0 = SK - WIN;
constexpr int FF = 1792;

constexpr int NCTA = 128;
constexpr int NCW = 8;
constexpr int NCT = NCW * 32;
constexpr int NTHREADS = (NCW + 2) * 32;

constexpr int CH_WQ = 0, CH_W1 = 8, CH_K = 10, CH_V = 18, CH_W2 = 26, CH_WO = 28, NCHUNK = 36;
constexpr int NSLOT = 13;
constexpr int NEMPTY = NCHUNK - NSLOT;
#define WINDOW 8
#define WINDOW2 4
__host__ __device__ constexpr int slot_off(int chunk) { return (chunk % NSLOT) * 8192; }

constexpr int BAR_FULL = 0;
constexpr int BAR_EMPTY = NCHUNK;
constexpr int BAR_Q = BAR_EMPTY + NEMPTY;
constexpr int BAR_ST = BAR_Q + 1;
constexpr int BAR_PO = BAR_ST + 1;
constexpr int BAR_O = BAR_PO + 1;
constexpr int NBAR = BAR_O + 1;

constexpr int SM_RING = 0;
constexpr int SM_INB = NSLOT * 8192;
constexpr int SM_INS = SM_INB + 2048;
constexpr int SM_REDA = SM_INS + 256;
constexpr int SM_REDG = SM_REDA + 512;
constexpr int SM_REDB = SM_REDA + 2048;
constexpr int SM_XN = SM_REDB + 1024;
constexpr int SM_P = SM_XN;
constexpr int SM_Q = SM_XN + 2048;
constexpr int SM_O = SM_Q;
constexpr int SM_MAX = SM_Q + 1024;
constexpr int SM_SUM = SM_MAX + 128;
constexpr int SM_BAR = SM_SUM + 128;
constexpr int SM_EPOCH = SM_BAR + NBAR * 8;
constexpr int SM_TOTAL = SM_EPOCH + 8;
static_assert(SM_TOTAL <= 115712, "two CTAs must fit on one SM");

constexpr unsigned SPIN_LIMIT = 1u << 22;

struct Scratch {
    unsigned epoch;
    unsigned pad[31];
    unsigned long long ax[2 * 112 * 8];
    unsigned long long pf[16 * 8 * 64];
    unsigned long long pa[16 * 8 * 64];
};

__device__ Scratch g_scratch;

struct Params {
    CUtensorMap wq, k, v, w1, wo, w2;
    const __nv_bfloat16* x;
    const __nv_bfloat16* b1;
    __nv_bfloat16* out;
    Scratch* sc;
};

__device__ __forceinline__ uint32_t smem_u32(const void* p) { return (uint32_t)__cvta_generic_to_shared(p); }
__device__ __forceinline__ void mbar_init(uint32_t bar, uint32_t cnt) {
    asm volatile("mbarrier.init.shared::cta.b64 [%0], %1;" ::"r"(bar), "r"(cnt) : "memory");
}
__device__ __forceinline__ void mbar_expect_tx(uint32_t bar, uint32_t bytes) {
    asm volatile("mbarrier.arrive.expect_tx.shared::cta.b64 _, [%0], %1;" ::"r"(bar), "r"(bytes) : "memory");
}
__device__ __forceinline__ void mbar_arrive(uint32_t bar) {
    asm volatile("mbarrier.arrive.shared::cta.b64 _, [%0];" ::"r"(bar) : "memory");
}
__device__ __forceinline__ void mbar_wait(uint32_t bar) {
    unsigned n = 0;
    uint32_t ok;
    do {
        asm volatile("{\n.reg .pred p;\nmbarrier.try_wait.parity.shared::cta.b64 p, [%1], 0;\nselp.u32 %0, 1, 0, p;\n}"
                     : "=r"(ok) : "r"(bar) : "memory");
    } while (!ok && ++n < SPIN_LIMIT);
}
__device__ __forceinline__ void mbar_wait_n(uint32_t bar0, int n, int lane) {
    const uint32_t bar = bar0 + (lane < n ? lane : 0) * 8;
    unsigned it = 0;
    uint32_t ok;
    do {
        asm volatile("{\n.reg .pred p;\nmbarrier.try_wait.parity.shared::cta.b64 p, [%1], 0;\nselp.u32 %0, 1, 0, p;\n}"
                     : "=r"(ok) : "r"(bar) : "memory");
    } while (!__all_sync(~0u, ok) && ++it < SPIN_LIMIT);
}
__device__ __forceinline__ void mbar_wait_cluster(uint32_t bar) {
    unsigned n = 0;
    uint32_t ok;
    do {
        asm volatile("{\n.reg .pred p;\nmbarrier.try_wait.parity.acquire.cluster.shared::cta.b64 p, [%1], 0;\nselp.u32 %0, 1, 0, p;\n}"
                     : "=r"(ok) : "r"(bar) : "memory");
    } while (!ok && ++n < SPIN_LIMIT);
}
__device__ __forceinline__ void tma2d(uint32_t dst, const CUtensorMap* tm, int c0, int c1, uint32_t bar) {
    asm volatile("cp.async.bulk.tensor.2d.shared::cluster.global.mbarrier::complete_tx::bytes [%0], [%1, {%3, %4}], [%2];"
                 ::"r"(dst), "l"((uint64_t)tm), "r"(bar), "r"(c0), "r"(c1) : "memory");
}
__device__ __forceinline__ uint32_t mapa(uint32_t addr, uint32_t rank) {
    uint32_t r;
    asm("mapa.shared::cluster.u32 %0, %1, %2;" : "=r"(r) : "r"(addr), "r"(rank));
    return r;
}
__device__ __forceinline__ void bar_sync(int id, int n) { asm volatile("bar.sync %0, %1;" ::"r"(id), "r"(n) : "memory"); }
__device__ __forceinline__ void bar_arrive(int id, int n) { asm volatile("bar.arrive %0, %1;" ::"r"(id), "r"(n) : "memory"); }

__device__ __forceinline__ void ldsm4(uint32_t (&r)[4], uint32_t addr) {
    asm volatile("ldmatrix.sync.aligned.m8n8.x4.shared.b16 {%0,%1,%2,%3}, [%4];"
                 : "=r"(r[0]), "=r"(r[1]), "=r"(r[2]), "=r"(r[3]) : "r"(addr) : "memory");
}
__device__ __forceinline__ void ldsm4t(uint32_t (&r)[4], uint32_t addr) {
    asm volatile("ldmatrix.sync.aligned.m8n8.x4.trans.shared.b16 {%0,%1,%2,%3}, [%4];"
                 : "=r"(r[0]), "=r"(r[1]), "=r"(r[2]), "=r"(r[3]) : "r"(addr) : "memory");
}
__device__ __forceinline__ void mma16816(float (&c)[4], uint32_t a0, uint32_t a1, uint32_t a2, uint32_t a3, uint32_t b0, uint32_t b1) {
    asm volatile("mma.sync.aligned.m16n8k16.row.col.f32.bf16.bf16.f32 {%0,%1,%2,%3}, {%4,%5,%6,%7}, {%8,%9}, {%0,%1,%2,%3};"
                 : "+f"(c[0]), "+f"(c[1]), "+f"(c[2]), "+f"(c[3])
                 : "r"(a0), "r"(a1), "r"(a2), "r"(a3), "r"(b0), "r"(b1));
}
__device__ __forceinline__ void st_ll1(unsigned long long* p, uint32_t d, uint32_t tag) {
    unsigned long long w = ((unsigned long long)tag << 32) | d;
    asm volatile("st.relaxed.gpu.global.b64 [%0], %1;" ::"l"(p), "l"(w) : "memory");
}
__device__ __forceinline__ void st_ll2(unsigned long long* p, uint32_t d0, uint32_t d1, uint32_t tag) {
    unsigned long long w0 = ((unsigned long long)tag << 32) | d0, w1 = ((unsigned long long)tag << 32) | d1;
    asm volatile("st.relaxed.gpu.global.v2.b64 [%0], {%1, %2};" ::"l"(p), "l"(w0), "l"(w1) : "memory");
}
__device__ __forceinline__ void ld_ll2(const unsigned long long* p, unsigned long long& w0, unsigned long long& w1) {
    asm volatile("ld.relaxed.gpu.global.v2.b64 {%0, %1}, [%2];" : "=l"(w0), "=l"(w1) : "l"(p) : "memory");
}
__device__ __forceinline__ bool tag_ok(unsigned long long w0, unsigned long long w1, uint32_t tag) {
    return (uint32_t)(w0 >> 32) == tag && (uint32_t)(w1 >> 32) == tag;
}
__device__ __forceinline__ float ex2(float x) {
    float y;
    asm("ex2.approx.ftz.f32 %0, %1;" : "=f"(y) : "f"(x));
    return y;
}
__device__ __forceinline__ float bf16r(float x) { return __bfloat162float(__float2bfloat16_rn(x)); }
__device__ __forceinline__ uint32_t pack_bf16(float lo, float hi) {
    __nv_bfloat162 v = __floats2bfloat162_rn(lo, hi);
    return *reinterpret_cast<uint32_t*>(&v);
}
__device__ __forceinline__ float bf_lo(uint32_t u) { return __uint_as_float(u << 16); }
__device__ __forceinline__ float bf_hi(uint32_t u) { return __uint_as_float(u & 0xffff0000u); }
__device__ __forceinline__ float2 lds_f2(uint32_t a) {
    float2 v;
    asm volatile("ld.shared.v2.f32 {%0, %1}, [%2];" : "=f"(v.x), "=f"(v.y) : "r"(a) : "memory");
    return v;
}
__device__ __forceinline__ float lds_f1(uint32_t a) {
    float v;
    asm volatile("ld.shared.f32 %0, [%1];" : "=f"(v) : "r"(a) : "memory");
    return v;
}
__device__ __forceinline__ uint32_t lds_u1(uint32_t a) {
    uint32_t v;
    asm volatile("ld.shared.u32 %0, [%1];" : "=r"(v) : "r"(a) : "memory");
    return v;
}
__device__ __forceinline__ void lds_u4(uint32_t* r, uint32_t a) {
    asm volatile("ld.shared.v4.u32 {%0,%1,%2,%3}, [%4];" : "=r"(r[0]), "=r"(r[1]), "=r"(r[2]), "=r"(r[3]) : "r"(a) : "memory");
}
__device__ __forceinline__ float4 lds_f4(uint32_t a) {
    float4 v;
    asm volatile("ld.shared.v4.f32 {%0,%1,%2,%3}, [%4];" : "=f"(v.x), "=f"(v.y), "=f"(v.z), "=f"(v.w) : "r"(a) : "memory");
    return v;
}
__device__ __forceinline__ void sts_f2(uint32_t a, float x, float y) {
    asm volatile("st.shared.v2.f32 [%0], {%1, %2};" ::"r"(a), "f"(x), "f"(y) : "memory");
}
__device__ __forceinline__ void sts_f4(uint32_t a, float x, float y, float z, float w) {
    asm volatile("st.shared.v4.f32 [%0], {%1,%2,%3,%4};" ::"r"(a), "f"(x), "f"(y), "f"(z), "f"(w) : "memory");
}
__device__ __forceinline__ void sts_f1(uint32_t a, float v) { asm volatile("st.shared.f32 [%0], %1;" ::"r"(a), "f"(v) : "memory"); }
__device__ __forceinline__ void sts_u1(uint32_t a, uint32_t v) { asm volatile("st.shared.u32 [%0], %1;" ::"r"(a), "r"(v) : "memory"); }
__device__ __forceinline__ void sts_u4(uint32_t a, uint32_t x, uint32_t y, uint32_t z, uint32_t w) {
    asm volatile("st.shared.v4.u32 [%0], {%1,%2,%3,%4};" ::"r"(a), "r"(x), "r"(y), "r"(z), "r"(w) : "memory");
}

#define TS(i) do { } while (0)

__device__ __forceinline__ void gemv_tile64(float (&acc)[2][4], uint32_t base, int row, int lchk, uint32_t b0, uint32_t b1) {
    uint32_t a0[4], a1[4];
    const uint32_t ra = base + row * 64;
    const int sw = (row >> 1) & 3;
    ldsm4t(a0, ra + ((lchk ^ sw) << 4));
    ldsm4t(a1, ra + (((2 + lchk) ^ sw) << 4));
    mma16816(acc[0], a0[0], a0[1], a0[2], a0[3], b0, b1);
    mma16816(acc[1], a1[0], a1[1], a1[2], a1[3], b0, b1);
}

__global__ void __cluster_dims__(8, 1, 1) __launch_bounds__(NTHREADS, 2) fused_decode_kernel(const __grid_constant__ Params p) {
    extern __shared__ __align__(1024) uint8_t smem[];
    const uint32_t sb = smem_u32(smem);
    const uint32_t bars = sb + SM_BAR;
    const int c = blockIdx.x;
    const int warp = threadIdx.x >> 5, lane = threadIdx.x & 31;
    const int bh = c >> 3, j = c & 7;
    const int r = c >> 4, g16 = c & 15;

    if (warp == NCW) {
        const int krow = bh * SK + WIN0 + j * 256;
        if (lane == 0) {
#pragma unroll
            for (int i = 0; i < CH_W1; i++) mbar_init(bars + i * 8, 1);
            asm volatile("fence.proxy.async.shared::cta;" ::: "memory");
#pragma unroll
            for (int i = 0; i < CH_W1; i++) {
                mbar_expect_tx(bars + i * 8, 8192);
                tma2d(sb + slot_off(i), &p.wq, (bh & 7) * 512 + 64 * j, 64 * i, bars + i * 8);
            }
#pragma unroll
            for (int k = CH_W1; k < NCHUNK; k++) mbar_init(bars + k * 8, 1);
            asm volatile("fence.proxy.async.shared::cta;" ::: "memory");
        }
        __syncwarp();
        asm volatile("barrier.cluster.arrive.relaxed.aligned;" ::: "memory");
        bar_sync(1, NTHREADS);
        if (lane == 0) {
#pragma unroll
            for (int i = CH_W1; i < NCHUNK; i++) {
                const uint32_t bar = bars + i * 8;
                const uint32_t dst = sb + slot_off(i);
                if (i >= CH_W2 && i - WINDOW2 < CH_W2) mbar_wait(bar - WINDOW2 * 8);
                else if (i >= WINDOW) mbar_wait(bar - WINDOW * 8);
                if (i >= NSLOT) mbar_wait(bars + (BAR_EMPTY + i - NSLOT) * 8);
                if (i < CH_K) {
                    const int q = i - CH_W1;
                    if (c < 112) {
                        mbar_expect_tx(bar, 8192);
                        tma2d(dst, &p.w1, 16 * c, 256 * q, bar);
                    } else {
                        mbar_expect_tx(bar, 0);
                    }
                } else if (i < CH_V) {
                    const int q = i - CH_K;
                    mbar_expect_tx(bar, 8192);
                    tma2d(dst, &p.k, 0, krow + q * 32, bar);
                    tma2d(dst + 4096, &p.k, 64, krow + q * 32, bar);
                } else if (i < CH_W2) {
                    const int q = i - CH_V;
                    mbar_expect_tx(bar, 8192);
                    tma2d(dst, &p.v, 0, krow + q * 32, bar);
                    tma2d(dst + 4096, &p.v, 64, krow + q * 32, bar);
                } else if (i < CH_WO) {
                    const int q = i - CH_W2;
                    mbar_expect_tx(bar, 7168);
                    tma2d(dst, &p.w2, 32 * g16, 224 * r + 112 * q, bar);
                } else {
                    const int q = i - CH_WO;
                    mbar_expect_tx(bar, 8192);
                    tma2d(dst, &p.wo, 64 * j, 512 * (bh & 7) + 64 * q, bar);
                }
            }
        }
        return;
    }

    Scratch* const sc = p.sc;
    const float LOG2E = 1.4426950408889634f;

    if (warp == NCW + 1) {
        const uint32_t tag = *reinterpret_cast<volatile unsigned*>(&sc->epoch) + 1u;
        const uint32_t xres = __ldg(reinterpret_cast<const uint32_t*>(p.x) + (bh >> 3) * 256 + j * 32 + lane);
        if (lane == 0) {
            mbar_init(bars + BAR_Q * 8, 1);
            mbar_init(bars + BAR_ST * 8, 1);
            mbar_init(bars + BAR_PO * 8, 1);
            mbar_init(bars + BAR_O * 8, 1);
            asm volatile("fence.mbarrier_init.release.cluster;" ::: "memory");
            mbar_expect_tx(bars + BAR_Q * 8, 1024);
            mbar_expect_tx(bars + BAR_ST * 8, 256);
            mbar_expect_tx(bars + BAR_PO * 8, 2048);
            mbar_expect_tx(bars + BAR_O * 8, 1024);
#pragma unroll
            for (int k = 0; k < NEMPTY; k++) mbar_init(bars + (BAR_EMPTY + k) * 8, (k >= CH_K && k < CH_V) ? 1 : NCW);
        }
        __syncwarp();
        asm volatile("barrier.cluster.arrive.relaxed.aligned;" ::: "memory");
        if (lane == 0) sts_u1(sb + SM_EPOCH, tag);
        __syncwarp();
        bar_arrive(1, NTHREADS);
        TS(0);
        asm volatile("barrier.cluster.wait.acquire.aligned;" ::: "memory");
        bar_sync(4, NCT + 32);
        {
            float mx = lds_f1(sb + SM_MAX + lane * 4);
            float sm = lds_f1(sb + SM_SUM + lane * 4);
#pragma unroll
            for (int o = 4; o < 32; o <<= 1) { mx = fmaxf(mx, __shfl_xor_sync(~0u, mx, o)); sm += __shfl_xor_sync(~0u, sm, o); }
            const uint32_t dst = mapa(sb + SM_INS + (j * 4 + (lane & 3)) * 8, lane >> 2);
            const uint32_t rbar = mapa(bars + BAR_ST * 8, lane >> 2);
            asm volatile("st.async.weak.shared::cluster.mbarrier::complete_tx::bytes.v2.f32 [%0], {%1, %2}, [%3];"
                         ::"r"(dst), "f"(mx), "f"(sm), "r"(rbar) : "memory");
        }
        TS(2);
        float coef[8];
        {
            mbar_wait_cluster(bars + BAR_ST * 8);
            const float2 st = lds_f2(sb + SM_INS + lane * 8);
            float gm = st.x;
#pragma unroll
            for (int o = 4; o < 32; o <<= 1) gm = fmaxf(gm, __shfl_xor_sync(~0u, gm, o));
            const float wj = ex2((st.x - gm) * LOG2E);
            float gl = wj * st.y;
#pragma unroll
            for (int o = 4; o < 32; o <<= 1) gl += __shfl_xor_sync(~0u, gl, o);
            const float cj = wj / gl;
#pragma unroll
            for (int k = 0; k < 8; k++) coef[k] = __shfl_sync(~0u, cj, k * 4 + (lane >> 3));
        }
        TS(3);
        mbar_wait_cluster(bars + BAR_PO * 8);
        {
            float o0 = 0.f, o1 = 0.f;
#pragma unroll
            for (int k = 0; k < 8; k++) {
                const float2 v = lds_f2(sb + SM_INB + k * 256 + lane * 8);
                o0 = fmaf(coef[k], v.x, o0);
                o1 = fmaf(coef[k], v.y, o1);
            }
            const uint32_t op = pack_bf16(o0, o1);
            const int t = (lane >> 1) & 3, q = (lane >> 3) * 2 + (j >> 2);
            const uint32_t dst = sb + SM_O + (((j >> 1) & 1) * 4 + t) * 128 + ((q ^ (2 * t)) << 4) + ((j & 1) * 2 + (lane & 1)) * 4;
#pragma unroll
            for (int k = 0; k < 8; k++)
                asm volatile("st.async.weak.shared::cluster.mbarrier::complete_tx::bytes.u32 [%0], %1, [%2];"
                             ::"r"(mapa(dst, k)), "r"(op), "r"(mapa(bars + BAR_O * 8, k)) : "memory");
        }
        TS(4);
        if ((bh & 7) != 0) return;
        float2 s = make_float2(bf_lo(xres), bf_hi(xres));
#pragma unroll
        for (int part = 0; part < 2; part++) {
            const unsigned long long* src = part == 0 ? &sc->pf[((2 * j + (lane >> 4)) * 8) * 64 + (bh >> 3) * 32 + (lane & 15) * 2]
                                                      : &sc->pa[(((bh >> 3) * 8 + j) * 8) * 64 + lane * 2];
            unsigned long long v[8][2] = {};
            unsigned n = 0;
            while (true) {
#pragma unroll
                for (int i = 0; i < 8; i++)
                    if (!tag_ok(v[i][0], v[i][1], tag)) ld_ll2(src + i * 64, v[i][0], v[i][1]);
                bool ok = true;
#pragma unroll
                for (int i = 0; i < 8; i++) ok = ok && tag_ok(v[i][0], v[i][1], tag);
                if (ok || ++n >= SPIN_LIMIT) break;
            }
#pragma unroll
            for (int i = 0; i < 8; i++) { s.x += __uint_as_float((uint32_t)v[i][0]); s.y += __uint_as_float((uint32_t)v[i][1]); }
        }
        reinterpret_cast<uint32_t*>(p.out)[(bh >> 3) * 256 + j * 32 + lane] = pack_bf16(s.x, s.y);
        __syncwarp();
        if (c == 0 && lane == 0) sc->epoch = tag;
        TS(16);
        return;
    }

    const int u = warp;
    const int fg = lane >> 2, ft = lane & 3;
    asm volatile("barrier.cluster.arrive.relaxed.aligned;" ::: "memory");

    uint32_t b1pair = 0;
    if (u < 2) {
        const uint4* x4 = reinterpret_cast<const uint4*>(p.x) + u * 64 + lane * 2;
        const uint4 v0 = __ldg(x4), v1 = __ldg(x4 + 1);
        if (u == 1 && c < 112) b1pair = __ldg(reinterpret_cast<const uint32_t*>(p.b1) + c * 8 + (lane & 7));
        const uint32_t a[8] = {v0.x, v0.y, v0.z, v0.w, v1.x, v1.y, v1.z, v1.w};
        float s0 = 0.f;
#pragma unroll
        for (int i = 0; i < 8; i++) s0 += bf_lo(a[i]) + bf_hi(a[i]);
#pragma unroll
        for (int o = 16; o > 0; o >>= 1) s0 += __shfl_xor_sync(~0u, s0, o);
        const float m0 = s0 * (1.f / D_MODEL);
        float q0 = 0.f;
#pragma unroll
        for (int i = 0; i < 8; i++) {
            float d;
            d = bf_lo(a[i]) - m0; q0 += d * d; d = bf_hi(a[i]) - m0; q0 += d * d;
        }
#pragma unroll
        for (int o = 16; o > 0; o >>= 1) q0 += __shfl_xor_sync(~0u, q0, o);
        const float mean = bf16r(m0);
        const float var = bf16r(q0 * (1.f / D_MODEL));
        const float den = bf16r(sqrtf(bf16r(var + 1e-5f)));
        const float rden = 1.f / den;
        uint32_t o[8];
#pragma unroll
        for (int i = 0; i < 8; i++) o[i] = pack_bf16(bf16r(bf_lo(a[i]) - mean) * rden, bf16r(bf_hi(a[i]) - mean) * rden);
        const uint32_t dst = sb + SM_XN + u * 1024 + lane * 32;
        sts_u4(dst, o[0], o[1], o[2], o[3]);
        sts_u4(dst + 16, o[4], o[5], o[6], o[7]);
        TS(0);
    }

    const int lrow = (lane & 7) + ((lane >> 4) << 3);
    const int lchk = (lane >> 3) & 1;

    bar_sync(1, NTHREADS);
    const uint32_t tag = lds_u1(sb + SM_EPOCH);

    auto gemv512 = [&](const int ch0, const uint32_t (&bb)[8][4], const bool release) {
        float acc[4] = {}, acc2[4] = {};
        const int row = (u >> 2) * 32 + lrow;
        const uint32_t wa = sb + row * 128 + ((((u & 3) * 2 + lchk) ^ (row & 7)) << 4);
        constexpr int GE[5] = {0, 4, 6, 7, 8};
#pragma unroll
        for (int g = 0; g < 4; g++) {
            mbar_wait_n(bars + (ch0 + GE[g]) * 8, GE[g + 1] - GE[g], lane);
            uint32_t a[4][2][4];
#pragma unroll
            for (int q = GE[g]; q < GE[g + 1]; q++) {
                ldsm4t(a[q - GE[g]][0], wa + slot_off(ch0 + q));
                ldsm4t(a[q - GE[g]][1], wa + slot_off(ch0 + q) + 2048);
            }
#pragma unroll
            for (int q = GE[g]; q < GE[g + 1]; q++) {
                const uint32_t(&a0)[4] = a[q - GE[g]][0];
                const uint32_t(&a1)[4] = a[q - GE[g]][1];
                mma16816(acc, a0[0], a0[1], a0[2], a0[3], bb[q][0], bb[q][1]);
                mma16816(acc2, a1[0], a1[1], a1[2], a1[3], bb[q][2], bb[q][3]);
            }
            if (release && lane < GE[g + 1] - GE[g]) mbar_arrive(bars + (BAR_EMPTY + ch0 + GE[g] + lane) * 8);
        }
        if (ft == 0) {
            sts_f1(sb + SM_REDA + ((u >> 2) * 64 + (u & 3) * 16 + fg) * 4, acc[0] + acc2[0]);
            sts_f1(sb + SM_REDA + ((u >> 2) * 64 + (u & 3) * 16 + fg + 8) * 4, acc[2] + acc2[2]);
        }
    };

    {
        uint32_t bb[8][4];
        const uint32_t xa = sb + SM_XN + (bh >> 3) * 1024 + ((u >> 2) * 16 + ft) * 4;
#pragma unroll
        for (int q = 0; q < 8; q++)
#pragma unroll
            for (int i = 0; i < 4; i++) bb[q][i] = lds_u1(xa + q * 128 + i * 16);
        gemv512(CH_WQ, bb, true);
    }
    TS(1);
    asm volatile("barrier.cluster.wait.acquire.aligned;" ::: "memory");
    bar_sync(2, NCT);
    if (u == 0) {
        const float2 s0 = lds_f2(sb + SM_REDA + lane * 8), s1 = lds_f2(sb + SM_REDA + 256 + lane * 8);
        const uint32_t qp = pack_bf16(s0.x + s1.x, s0.y + s1.y);
        const uint32_t dst = sb + SM_Q + (((j >> 1) * 4 + (lane & 3)) * 16 + (j & 1) * 8 + (lane >> 2)) * 4;
#pragma unroll
        for (int k = 0; k < 8; k++)
            asm volatile("st.async.weak.shared::cluster.mbarrier::complete_tx::bytes.u32 [%0], %1, [%2];"
                         ::"r"(mapa(dst, k)), "r"(qp), "r"(mapa(bars + BAR_Q * 8, k)) : "memory");
        TS(2);
    }

    if (c < 112) {
        uint32_t xb[4][2];
#pragma unroll
        for (int q = 0; q < 4; q++) {
            xb[q][0] = lds_u1(sb + SM_XN + (fg & 1) * 1024 + (q * 64 + u * 8 + ft) * 4);
            xb[q][1] = lds_u1(sb + SM_XN + (fg & 1) * 1024 + (q * 64 + u * 8 + 4 + ft) * 4);
        }
        float acc[4] = {};
#pragma unroll
        for (int q = 0; q < 4; q++) {
            if ((q & 1) == 0) mbar_wait(bars + (CH_W1 + (q >> 1)) * 8);
            const int row = (q & 1) * 128 + u * 16 + lrow;
            uint32_t a[4];
            ldsm4t(a, sb + slot_off(CH_W1 + (q >> 1)) + row * 32 + ((lchk ^ ((row >> 2) & 1)) << 4));
            mma16816(acc, a[0], a[1], a[2], a[3], xb[q][0], xb[q][1]);
            if ((q & 1) && lane == 0) mbar_arrive(bars + (BAR_EMPTY + CH_W1 + (q >> 1)) * 8);
        }
        TS(10);
        if (ft == 0) {
            const uint32_t rb = sb + SM_REDB + u * 128;
            sts_f1(rb + fg * 4, acc[0]);
            sts_f1(rb + 64 + fg * 4, acc[1]);
            sts_f1(rb + (fg + 8) * 4, acc[2]);
            sts_f1(rb + 64 + (fg + 8) * 4, acc[3]);
        }
        bar_sync(2, NCT);
        if (u == 1 && lane < 16) {
            float2 s = make_float2(0.f, 0.f);
#pragma unroll
            for (int k = 0; k < NCW; k++) {
                float2 v = lds_f2(sb + SM_REDB + k * 128 + lane * 8);
                s.x += v.x; s.y += v.y;
            }
            float h[2] = {bf16r(bf16r(s.x) + bf_lo(b1pair)), bf16r(bf16r(s.y) + bf_hi(b1pair))};
            float a[2];
#pragma unroll
            for (int i = 0; i < 2; i++) {
                const float e = bf16r(__expf(-fabsf(h[i])));
                const float sp = bf16r(bf16r(log1pf(e)) + fmaxf(h[i], 0.f));
                a[i] = h[i] * bf16r(tanhf(sp));
            }
            const int dp = lane & 7;
            st_ll1(&sc->ax[(((lane >> 3) * 112 + c) * 4 + (dp & 3)) * 2 + (dp >> 2)], pack_bf16(a[0], a[1]), tag);
            TS(7);
        }
    } else if (lane == 0) {
        mbar_arrive(bars + (BAR_EMPTY + CH_W1) * 8);
        mbar_arrive(bars + (BAR_EMPTY + CH_W1 + 1) * 8);
    }
    __syncwarp();

    {
        mbar_wait_cluster(bars + BAR_Q * 8);
        TS(3);
        uint32_t qa[16];
#pragma unroll
        for (int i = 0; i < 4; i++) lds_u4(qa + 4 * i, sb + SM_Q + ((fg & 3) * 4 + ft) * 64 + i * 16);
        mbar_wait(bars + (CH_K + u) * 8);
        TS(4);
        float acc[4][4] = {};
        const uint32_t kb = sb + ((CH_K + u) % NSLOT) * 8192 + (lane & 7) * 128;
#pragma unroll
        for (int q = 0; q < 4; q++) {
            const int chunk = q * 4 + (lane >> 3);
            const uint32_t off = (chunk >> 3) * 4096 + (((chunk & 7) ^ (lane & 7)) << 4);
#pragma unroll
            for (int nt = 0; nt < 4; nt++) {
                uint32_t b[4];
                ldsm4(b, kb + nt * 1024 + off);
                mma16816(acc[nt], qa[4 * q], 0u, qa[4 * q + 1], 0u, b[0], b[1]);
                mma16816(acc[nt], qa[4 * q + 2], 0u, qa[4 * q + 3], 0u, b[2], b[3]);
            }
        }
        if (lane == 0) mbar_arrive(bars + (BAR_EMPTY + CH_K + u) * 8);
        const float scale = 0.08838834764831845f;
        float sv[8];
#pragma unroll
        for (int i = 0; i < 8; i++) sv[i] = bf16r(bf16r(acc[i >> 1][i & 1]) * scale);
        float m = fmaxf(fmaxf(fmaxf(sv[0], sv[1]), fmaxf(sv[2], sv[3])), fmaxf(fmaxf(sv[4], sv[5]), fmaxf(sv[6], sv[7])));
        m = fmaxf(m, __shfl_xor_sync(~0u, m, 1));
        m = fmaxf(m, __shfl_xor_sync(~0u, m, 2));
        if (lane < 16 && ft == 0) sts_f1(sb + SM_MAX + (u * 4 + fg) * 4, m);
        TS(5);
        bar_sync(2, NCT);
        m = lds_f1(sb + SM_MAX + ((ft + 4 * (fg >> 2)) * 4 + (fg & 3)) * 4);
        m = fmaxf(m, __shfl_xor_sync(~0u, m, 1));
        m = fmaxf(m, __shfl_xor_sync(~0u, m, 2));
        m = fmaxf(m, __shfl_xor_sync(~0u, m, 16));
#pragma unroll
        for (int i = 0; i < 8; i++) sv[i] = ex2((sv[i] - m) * LOG2E);
        float l = ((sv[0] + sv[1]) + (sv[2] + sv[3])) + ((sv[4] + sv[5]) + (sv[6] + sv[7]));
        l += __shfl_xor_sync(~0u, l, 1);
        l += __shfl_xor_sync(~0u, l, 2);
        if (lane < 16) {
            sts_u4(sb + SM_P + (u * 16 + lane) * 16, pack_bf16(sv[0], sv[1]), pack_bf16(sv[2], sv[3]), pack_bf16(sv[4], sv[5]),
                   pack_bf16(sv[6], sv[7]));
            if (ft == 0) sts_f1(sb + SM_SUM + (u * 4 + fg) * 4, l);
        }
        bar_sync(4, NCT + 32);
        TS(6);
    }

    unsigned long long w[2][2] = {};
    const unsigned long long* sa = &sc->ax[(((fg & 1) * 112 + r * 14 + (u < 7 ? u : 0)) * 4 + ft) * 2];
    if (lane < 8) {
        ld_ll2(sa, w[0][0], w[0][1]);
        ld_ll2(sa + 56, w[1][0], w[1][1]);
    }
    {
        float acc[2][4] = {};
        const uint32_t voff = (u >> 2) * 4096 + lane * 128;
        const uint32_t c0 = (((u & 3) * 2) ^ (lane & 7)) << 4, c1 = (((u & 3) * 2 + 1) ^ (lane & 7)) << 4;
#pragma unroll
        for (int i = 0; i < 8; i++) {
            uint32_t pa[4], b0[4], b1[4];
            lds_u4(pa, sb + SM_P + (i * 16 + (lane & 15)) * 16);
            mbar_wait(bars + (CH_V + i) * 8);
            ldsm4t(b0, sb + slot_off(CH_V + i) + voff + c0);
            ldsm4t(b1, sb + slot_off(CH_V + i) + voff + c1);
            mma16816(acc[0], pa[0], 0u, pa[1], 0u, b0[0], b0[1]);
            mma16816(acc[1], pa[0], 0u, pa[1], 0u, b1[0], b1[1]);
            mma16816(acc[0], pa[2], 0u, pa[3], 0u, b0[2], b0[3]);
            mma16816(acc[1], pa[2], 0u, pa[3], 0u, b1[2], b1[3]);
            if (CH_V + i < NEMPTY && lane == 0) mbar_arrive(bars + (BAR_EMPTY + CH_V + i) * 8);
        }
        TS(8);
        if (lane < 16) {
            const uint32_t dst = mapa(sb + SM_INB + j * 256 + lane * 16, u);
            const uint32_t rbar = mapa(bars + BAR_PO * 8, u);
            asm volatile("st.async.weak.shared::cluster.mbarrier::complete_tx::bytes.v4.f32 [%0], {%1, %2, %3, %4}, [%5];"
                         ::"r"(dst), "f"(acc[0][0]), "f"(acc[0][1]), "f"(acc[1][0]), "f"(acc[1][1]), "r"(rbar) : "memory");
        }
        TS(9);
    }

    {
        if (lane < 8) {
            unsigned n = 0;
            while (!(tag_ok(w[0][0], w[0][1], tag) && tag_ok(w[1][0], w[1][1], tag)) && ++n < SPIN_LIMIT) {
                ld_ll2(sa, w[0][0], w[0][1]);
                ld_ll2(sa + 56, w[1][0], w[1][1]);
            }
        }
        __syncwarp();
        if (u < 7) {
            float acc[2][4] = {}, acc2[2][4] = {};
            mbar_wait_n(bars + CH_W2 * 8, 2, lane);
            gemv_tile64(acc, sb + slot_off(CH_W2), u * 16 + lrow, lchk, (uint32_t)w[0][0], (uint32_t)w[0][1]);
            gemv_tile64(acc2, sb + slot_off(CH_W2 + 1), u * 16 + lrow, lchk, (uint32_t)w[1][0], (uint32_t)w[1][1]);
#pragma unroll
            for (int mt = 0; mt < 2; mt++)
#pragma unroll
                for (int i = 0; i < 4; i++) acc[mt][i] += acc2[mt][i];
            if (ft == 0) {
                const uint32_t rb = sb + SM_REDG + u * 256;
#pragma unroll
                for (int mt = 0; mt < 2; mt++) {
                    sts_f1(rb + (mt * 16 + fg) * 4, acc[mt][0]);
                    sts_f1(rb + 128 + (mt * 16 + fg) * 4, acc[mt][1]);
                    sts_f1(rb + (mt * 16 + fg + 8) * 4, acc[mt][2]);
                    sts_f1(rb + 128 + (mt * 16 + fg + 8) * 4, acc[mt][3]);
                }
            }
            bar_arrive(3, NCT);
        } else {
            bar_sync(3, NCT);
            float2 s = make_float2(0.f, 0.f);
#pragma unroll
            for (int k = 0; k < 7; k++) {
                const float2 t = lds_f2(sb + SM_REDG + k * 256 + lane * 8);
                s.x += t.x; s.y += t.y;
            }
            st_ll2(&sc->pf[(g16 * 8 + r) * 64 + lane * 2], __float_as_uint(s.x), __float_as_uint(s.y), tag);
        }
        TS(11);
    }

    mbar_wait_cluster(bars + BAR_O * 8);
    TS(12);
    {
        uint32_t bb[8][4];
#pragma unroll
        for (int q = 0; q < 8; q++) lds_u4(bb[q], sb + SM_O + ((u >> 2) * 4 + ft) * 128 + ((q ^ (2 * ft)) << 4));
        gemv512(CH_WO, bb, false);
    }
    TS(14);
    if (u != 0) { bar_arrive(2, NCT); return; }
    bar_sync(2, NCT);
    {
        const float2 s0 = lds_f2(sb + SM_REDA + lane * 8), s1 = lds_f2(sb + SM_REDA + 256 + lane * 8);
        st_ll2(&sc->pa[((((bh >> 3) * 8 + j) * 8) + (bh & 7)) * 64 + lane * 2], __float_as_uint(s0.x + s1.x),
               __float_as_uint(s0.y + s1.y), tag);
        TS(15);
    }
}

typedef CUresult (*EncodeTiledFn)(CUtensorMap*, CUtensorMapDataType, cuuint32_t, void*, const cuuint64_t*, const cuuint64_t*,
                                  const cuuint32_t*, const cuuint32_t*, CUtensorMapInterleave, CUtensorMapSwizzle,
                                  CUtensorMapL2promotion, CUtensorMapFloatOOBfill);

void make_map(EncodeTiledFn enc, CUtensorMap* m, const void* base, uint64_t cols, uint64_t rows, uint32_t box_c, uint32_t box_r,
              CUtensorMapSwizzle sw) {
    cuuint64_t gd[2] = {cols, rows};
    cuuint64_t gs[1] = {cols * 2};
    cuuint32_t bd[2] = {box_c, box_r};
    cuuint32_t es[2] = {1, 1};
    enc(m, CU_TENSOR_MAP_DATA_TYPE_BFLOAT16, 2, const_cast<void*>(base), gd, gs, bd, es, CU_TENSOR_MAP_INTERLEAVE_NONE, sw,
        CU_TENSOR_MAP_L2_PROMOTION_L2_128B, CU_TENSOR_MAP_FLOAT_OOB_FILL_NONE);
}

}

extern "C" void kernel_launch(void* const* d_in, const int* in_sizes, int n_in, void* d_out, int out_size) {
    (void)in_sizes; (void)n_in; (void)out_size;
    static EncodeTiledFn enc = nullptr;
    static Scratch* sc = nullptr;
    if (!enc) {
        void* fn = nullptr;
        cudaDriverEntryPointQueryResult st;
        cudaGetDriverEntryPoint("cuTensorMapEncodeTiled", &fn, cudaEnableDefault, &st);
        enc = (EncodeTiledFn)fn;
        cudaFuncSetAttribute(fused_decode_kernel, cudaFuncAttributeMaxDynamicSharedMemorySize, SM_TOTAL);
        void* sp = nullptr;
        cudaGetSymbolAddress(&sp, g_scratch);
        sc = (Scratch*)sp;
    }
    Params p;
    make_map(enc, &p.k, d_in[1], 128, 2 * 8 * SK, 64, 32, CU_TENSOR_MAP_SWIZZLE_128B);
    make_map(enc, &p.v, d_in[2], 128, 2 * 8 * SK, 64, 32, CU_TENSOR_MAP_SWIZZLE_128B);
    make_map(enc, &p.wq, d_in[3], 4096, 512, 64, 64, CU_TENSOR_MAP_SWIZZLE_128B);
    make_map(enc, &p.wo, d_in[4], 512, 4096, 64, 64, CU_TENSOR_MAP_SWIZZLE_128B);
    make_map(enc, &p.w1, d_in[6], FF, 512, 16, 256, CU_TENSOR_MAP_SWIZZLE_32B);
    make_map(enc, &p.w2, d_in[8], 512, FF, 32, 112, CU_TENSOR_MAP_SWIZZLE_64B);
    p.x = (const __nv_bfloat16*)d_in[0];
    p.b1 = (const __nv_bfloat16*)d_in[7];
    p.out = (__nv_bfloat16*)d_out;
    p.sc = sc;
    fused_decode_kernel<<<NCTA, NTHREADS, SM_TOTAL, cudaStreamPerThread>>>(p);
}
```

```cpp
#include <cuda_runtime.h>
#include <cuda_bf16.h>
#include <cuda.h>
#include <stdint.h>

namespace {

constexpr int D_MODEL = 512;
constexpr int SK = 8192;
constexpr int WIN = 2048;
constexpr int WIN0 = SK - WIN;
constexpr int FF = 1792;

constexpr int NCTA = 128;
constexpr int NCW = 8;
constexpr int NCT = NCW * 32;
constexpr int NTHREADS = (NCW + 2) * 32;

constexpr int CH_WQ = 0, CH_W1 = 8, CH_K = 10, CH_V = 18, CH_W2 = 26, CH_WO = 28, NCHUNK = 36;
constexpr int NSLOT = 13;
constexpr int NEMPTY = NCHUNK - NSLOT;
#define WINDOW 8
#define WINDOW2 4
__host__ __device__ constexpr int slot_off(int chunk) { return (chunk % NSLOT) * 8192; }

constexpr int BAR_FULL = 0;
constexpr int BAR_EMPTY = NCHUNK;
constexpr int BAR_Q = BAR_EMPTY + NEMPTY;
constexpr int BAR_ST = BAR_Q + 1;
constexpr int BAR_PO = BAR_ST + 1;
constexpr int BAR_O = BAR_PO + 1;
constexpr int NBAR = BAR_O + 1;

constexpr int SM_RING = 0;
constexpr int SM_INB = NSLOT * 8192;
constexpr int SM_INS = SM_INB + 2048;
constexpr int SM_REDA = SM_INS + 256;
constexpr int SM_REDG = SM_REDA + 512;
constexpr int SM_REDB = SM_REDA + 2048;
constexpr int SM_XN = SM_REDB + 1024;
constexpr int SM_P = SM_XN;
constexpr int SM_Q = SM_XN + 2048;
constexpr int SM_O = SM_Q;
constexpr int SM_MAX = SM_Q + 1024;
constexpr int SM_SUM = SM_MAX + 128;
constexpr int SM_BAR = SM_SUM + 128;
constexpr int SM_EPOCH = SM_BAR + NBAR * 8;
constexpr int SM_TOTAL = SM_EPOCH + 8;
static_assert(SM_TOTAL <= 115712, "two CTAs must fit on one SM");

constexpr unsigned SPIN_LIMIT = 1u << 22;

struct Scratch {
    unsigned epoch;
    unsigned pad[31];
    unsigned long long ax[2 * 112 * 8];
    unsigned long long pf[16 * 8 * 64];
    unsigned long long pa[16 * 8 * 64];
};

__device__ Scratch g_scratch;

struct Params {
    CUtensorMap wq, k, v, w1, wo, w2;
    const __nv_bfloat16* x;
    const __nv_bfloat16* b1;
    __nv_bfloat16* out;
    Scratch* sc;
};

__device__ __forceinline__ uint32_t smem_u32(const void* p) { return (uint32_t)__cvta_generic_to_shared(p); }
__device__ __forceinline__ void mbar_init(uint32_t bar, uint32_t cnt) {
    asm volatile("mbarrier.init.shared::cta.b64 [%0], %1;" ::"r"(bar), "r"(cnt) : "memory");
}
__device__ __forceinline__ void mbar_expect_tx(uint32_t bar, uint32_t bytes) {
    asm volatile("mbarrier.arrive.expect_tx.shared::cta.b64 _, [%0], %1;" ::"r"(bar), "r"(bytes) : "memory");
}
__device__ __forceinline__ void mbar_arrive(uint32_t bar) {
    asm volatile("mbarrier.arrive.shared::cta.b64 _, [%0];" ::"r"(bar) : "memory");
}
__device__ __forceinline__ void mbar_wait(uint32_t bar) {
    unsigned n = 0;
    uint32_t ok;
    do {
        asm volatile("{\n.reg .pred p;\nmbarrier.try_wait.parity.shared::cta.b64 p, [%1], 0;\nselp.u32 %0, 1, 0, p;\n}"
                     : "=r"(ok) : "r"(bar) : "memory");
    } while (!ok && ++n < SPIN_LIMIT);
}
__device__ __forceinline__ void mbar_wait_n(uint32_t bar0, int n, int lane) {
    const uint32_t bar = bar0 + (lane < n ? lane : 0) * 8;
    unsigned it = 0;
    uint32_t ok;
    do {
        asm volatile("{\n.reg .pred p;\nmbarrier.try_wait.parity.shared::cta.b64 p, [%1], 0;\nselp.u32 %0, 1, 0, p;\n}"
                     : "=r"(ok) : "r"(bar) : "memory");
    } while (!__all_sync(~0u, ok) && ++it < SPIN_LIMIT);
}
__device__ __forceinline__ void mbar_wait_cluster(uint32_t bar) {
    unsigned n = 0;
    uint32_t ok;
    do {
        asm volatile("{\n.reg .pred p;\nmbarrier.try_wait.parity.acquire.cluster.shared::cta.b64 p, [%1], 0;\nselp.u32 %0, 1, 0, p;\n}"
                     : "=r"(ok) : "r"(bar) : "memory");
    } while (!ok && ++n < SPIN_LIMIT);
}
__device__ __forceinline__ void tma2d(uint32_t dst, const CUtensorMap* tm, int c0, int c1, uint32_t bar) {
    asm volatile("cp.async.bulk.tensor.2d.shared::cluster.global.mbarrier::complete_tx::bytes [%0], [%1, {%3, %4}], [%2];"
                 ::"r"(dst), "l"((uint64_t)tm), "r"(bar), "r"(c0), "r"(c1) : "memory");
}
__device__ __forceinline__ uint32_t mapa(uint32_t addr, uint32_t rank) {
    uint32_t r;
    asm("mapa.shared::cluster.u32 %0, %1, %2;" : "=r"(r) : "r"(addr), "r"(rank));
    return r;
}
__device__ __forceinline__ void bar_sync(int id, int n) { asm volatile("bar.sync %0, %1;" ::"r"(id), "r"(n) : "memory"); }
__device__ __forceinline__ void bar_arrive(int id, int n) { asm volatile("bar.arrive %0, %1;" ::"r"(id), "r"(n) : "memory"); }

__device__ __forceinline__ void ldsm4(uint32_t (&r)[4], uint32_t addr) {
    asm volatile("ldmatrix.sync.aligned.m8n8.x4.shared.b16 {%0,%1,%2,%3}, [%4];"
                 : "=r"(r[0]), "=r"(r[1]), "=r"(r[2]), "=r"(r[3]) : "r"(addr) : "memory");
}
__device__ __forceinline__ void ldsm4t(uint32_t (&r)[4], uint32_t addr) {
    asm volatile("ldmatrix.sync.aligned.m8n8.x4.trans.shared.b16 {%0,%1,%2,%3}, [%4];"
                 : "=r"(r[0]), "=r"(r[1]), "=r"(r[2]), "=r"(r[3]) : "r"(addr) : "memory");
}
__device__ __forceinline__ void mma16816(float (&c)[4], uint32_t a0, uint32_t a1, uint32_t a2, uint32_t a3, uint32_t b0, uint32_t b1) {
    asm volatile("mma.sync.aligned.m16n8k16.row.col.f32.bf16.bf16.f32 {%0,%1,%2,%3}, {%4,%5,%6,%7}, {%8,%9}, {%0,%1,%2,%3};"
                 : "+f"(c[0]), "+f"(c[1]), "+f"(c[2]), "+f"(c[3])
                 : "r"(a0), "r"(a1), "r"(a2), "r"(a3), "r"(b0), "r"(b1));
}
__device__ __forceinline__ void st_ll1(unsigned long long* p, uint32_t d, uint32_t tag) {
    unsigned long long w = ((unsigned long long)tag << 32) | d;
    asm volatile("st.relaxed.gpu.global.b64 [%0], %1;" ::"l"(p), "l"(w) : "memory");
}
__device__ __forceinline__ void st_ll2(unsigned long long* p, uint32_t d0, uint32_t d1, uint32_t tag) {
    unsigned long long w0 = ((unsigned long long)tag << 32) | d0, w1 = ((unsigned long long)tag << 32) | d1;
    asm volatile("st.relaxed.gpu.global.v2.b64 [%0], {%1, %2};" ::"l"(p), "l"(w0), "l"(w1) : "memory");
}
__device__ __forceinline__ void ld_ll2(const unsigned long long* p, unsigned long long& w0, unsigned long long& w1) {
    asm volatile("ld.relaxed.gpu.global.v2.b64 {%0, %1}, [%2];" : "=l"(w0), "=l"(w1) : "l"(p) : "memory");
}
__device__ __forceinline__ bool tag_ok(unsigned long long w0, unsigned long long w1, uint32_t tag) {
    return (uint32_t)(w0 >> 32) == tag && (uint32_t)(w1 >> 32) == tag;
}
__device__ __forceinline__ float ex2(float x) {
    float y;
    asm("ex2.approx.ftz.f32 %0, %1;" : "=f"(y) : "f"(x));
    return y;
}
__device__ __forceinline__ float bf16r(float x) { return __bfloat162float(__float2bfloat16_rn(x)); }
__device__ __forceinline__ uint32_t pack_bf16(float lo, float hi) {
    __nv_bfloat162 v = __floats2bfloat162_rn(lo, hi);
    return *reinterpret_cast<uint32_t*>(&v);
}
__device__ __forceinline__ float bf_lo(uint32_t u) { return __uint_as_float(u << 16); }
__device__ __forceinline__ float bf_hi(uint32_t u) { return __uint_as_float(u & 0xffff0000u); }
__device__ __forceinline__ float2 lds_f2(uint32_t a) {
    float2 v;
    asm volatile("ld.shared.v2.f32 {%0, %1}, [%2];" : "=f"(v.x), "=f"(v.y) : "r"(a) : "memory");
    return v;
}
__device__ __forceinline__ float lds_f1(uint32_t a) {
    float v;
    asm volatile("ld.shared.f32 %0, [%1];" : "=f"(v) : "r"(a) : "memory");
    return v;
}
__device__ __forceinline__ uint32_t lds_u1(uint32_t a) {
    uint32_t v;
    asm volatile("ld.shared.u32 %0, [%1];" : "=r"(v) : "r"(a) : "memory");
    return v;
}
__device__ __forceinline__ void lds_u4(uint32_t* r, uint32_t a) {
    asm volatile("ld.shared.v4.u32 {%0,%1,%2,%3}, [%4];" : "=r"(r[0]), "=r"(r[1]), "=r"(r[2]), "=r"(r[3]) : "r"(a) : "memory");
}
__device__ __forceinline__ float4 lds_f4(uint32_t a) {
    float4 v;
    asm volatile("ld.shared.v4.f32 {%0,%1,%2,%3}, [%4];" : "=f"(v.x), "=f"(v.y), "=f"(v.z), "=f"(v.w) : "r"(a) : "memory");
    return v;
}
__device__ __forceinline__ void sts_f2(uint32_t a, float x, float y) {
    asm volatile("st.shared.v2.f32 [%0], {%1, %2};" ::"r"(a), "f"(x), "f"(y) : "memory");
}
__device__ __forceinline__ void sts_f4(uint32_t a, float x, float y, float z, float w) {
    asm volatile("st.shared.v4.f32 [%0], {%1,%2,%3,%4};" ::"r"(a), "f"(x), "f"(y), "f"(z), "f"(w) : "memory");
}
__device__ __forceinline__ void sts_f1(uint32_t a, float v) { asm volatile("st.shared.f32 [%0], %1;" ::"r"(a), "f"(v) : "memory"); }
__device__ __forceinline__ void sts_u1(uint32_t a, uint32_t v) { asm volatile("st.shared.u32 [%0], %1;" ::"r"(a), "r"(v) : "memory"); }
__device__ __forceinline__ void sts_u4(uint32_t a, uint32_t x, uint32_t y, uint32_t z, uint32_t w) {
    asm volatile("st.shared.v4.u32 [%0], {%1,%2,%3,%4};" ::"r"(a), "r"(x), "r"(y), "r"(z), "r"(w) : "memory");
}

#define TS(i) do { } while (0)

__device__ __forceinline__ void gemv_tile64(float (&acc)[2][4], uint32_t base, int row, int lchk, uint32_t b0, uint32_t b1) {
    uint32_t a0[4], a1[4];
    const uint32_t ra = base + row * 64;
    const int sw = (row >> 1) & 3;
    ldsm4t(a0, ra + ((lchk ^ sw) << 4));
    ldsm4t(a1, ra + (((2 + lchk) ^ sw) << 4));
    mma16816(acc[0], a0[0], a0[1], a0[2], a0[3], b0, b1);
    mma16816(acc[1], a1[0], a1[1], a1[2], a1[3], b0, b1);
}

template <int CH0, bool RELEASE, int Q0, int Q1>
__device__ __forceinline__ void gemv_group(float (&acc)[4], float (&acc2)[4], const uint32_t (&bb)[8][4], uint32_t wa, uint32_t bars,
                                           int lane) {
    mbar_wait_n(bars + (CH0 + Q0) * 8, Q1 - Q0, lane);
    uint32_t a0[Q1 - Q0][4], a1[Q1 - Q0][4];
#pragma unroll
    for (int q = Q0; q < Q1; q++) {
        ldsm4t(a0[q - Q0], wa + slot_off(CH0 + q));
        ldsm4t(a1[q - Q0], wa + slot_off(CH0 + q) + 2048);
    }
#pragma unroll
    for (int q = Q0; q < Q1; q++) {
        mma16816(acc, a0[q - Q0][0], a0[q - Q0][1], a0[q - Q0][2], a0[q - Q0][3], bb[q][0], bb[q][1]);
        mma16816(acc2, a1[q - Q0][0], a1[q - Q0][1], a1[q - Q0][2], a1[q - Q0][3], bb[q][2], bb[q][3]);
    }
    if (RELEASE && lane < Q1 - Q0) mbar_arrive(bars + (BAR_EMPTY + CH0 + Q0 + lane) * 8);
}
template <int CH0, bool RELEASE>
__device__ __forceinline__ void gemv512(const uint32_t (&bb)[8][4], uint32_t wa, uint32_t bars, uint32_t red, int lane) {
    float acc[4] = {}, acc2[4] = {};
    gemv_group<CH0, RELEASE, 0, 4>(acc, acc2, bb, wa, bars, lane);
    gemv_group<CH0, RELEASE, 4, 6>(acc, acc2, bb, wa, bars, lane);
    gemv_group<CH0, RELEASE, 6, 7>(acc, acc2, bb, wa, bars, lane);
    gemv_group<CH0, RELEASE, 7, 8>(acc, acc2, bb, wa, bars, lane);
    if ((lane & 3) == 0) {
        sts_f1(red, acc[0] + acc2[0]);
        sts_f1(red + 32, acc[2] + acc2[2]);
    }
}

__global__ void __cluster_dims__(8, 1, 1) __launch_bounds__(NTHREADS, 2) fused_decode_kernel(const __grid_constant__ Params p) {
    extern __shared__ __align__(1024) uint8_t smem[];
    const uint32_t sb = smem_u32(smem);
    const uint32_t bars = sb + SM_BAR;
    const int c = blockIdx.x;
    const int warp = threadIdx.x >> 5, lane = threadIdx.x & 31;
    const int bh = c >> 3, j = c & 7;
    const int r = c >> 4, g16 = c & 15;

    if (warp == NCW) {
        const int krow = bh * SK + WIN0 + j * 256;
        if (lane == 0) {
#pragma unroll
            for (int i = 0; i < CH_W1; i++) mbar_init(bars + i * 8, 1);
            asm volatile("fence.proxy.async.shared::cta;" ::: "memory");
#pragma unroll
            for (int i = 0; i < CH_W1; i++) {
                mbar_expect_tx(bars + i * 8, 8192);
                tma2d(sb + slot_off(i), &p.wq, (bh & 7) * 512 + 64 * j, 64 * i, bars + i * 8);
            }
#pragma unroll
            for (int k = CH_W1; k < NCHUNK; k++) mbar_init(bars + k * 8, 1);
            asm volatile("fence.proxy.async.shared::cta;" ::: "memory");
        }
        __syncwarp();
        asm volatile("barrier.cluster.arrive.relaxed.aligned;" ::: "memory");
        bar_sync(1, NTHREADS);
        if (lane == 0) {
#pragma unroll
            for (int i = CH_W1; i < NCHUNK; i++) {
                const uint32_t bar = bars + i * 8;
                const uint32_t dst = sb + slot_off(i);
                if (i >= CH_W2 && i - WINDOW2 < CH_W2) mbar_wait(bar - WINDOW2 * 8);
                else if (i >= WINDOW) mbar_wait(bar - WINDOW * 8);
                if (i >= NSLOT) mbar_wait(bars + (BAR_EMPTY + i - NSLOT) * 8);
                if (i < CH_K) {
                    const int q = i - CH_W1;
                    if (c < 112) {
                        mbar_expect_tx(bar, 8192);
                        tma2d(dst, &p.w1, 16 * c, 256 * q, bar);
                    } else {
                        mbar_expect_tx(bar, 0);
                    }
                } else if (i < CH_V) {
                    const int q = i - CH_K;
                    mbar_expect_tx(bar, 8192);
                    tma2d(dst, &p.k, 0, krow + q * 32, bar);
                    tma2d(dst + 4096, &p.k, 64, krow + q * 32, bar);
                } else if (i < CH_W2) {
                    const int q = i - CH_V;
                    mbar_expect_tx(bar, 8192);
                    tma2d(dst, &p.v, 0, krow + q * 32, bar);
                    tma2d(dst + 4096, &p.v, 64, krow + q * 32, bar);
                } else if (i < CH_WO) {
                    const int q = i - CH_W2;
                    mbar_expect_tx(bar, 7168);
                    tma2d(dst, &p.w2, 32 * g16, 224 * r + 112 * q, bar);
                } else {
                    const int q = i - CH_WO;
                    mbar_expect_tx(bar, 8192);
                    tma2d(dst, &p.wo, 64 * j, 512 * (bh & 7) + 64 * q, bar);
                }
            }
        }
        return;
    }

    Scratch* const sc = p.sc;
    const float LOG2E = 1.4426950408889634f;

    if (warp == NCW + 1) {
        const uint32_t tag = *reinterpret_cast<volatile unsigned*>(&sc->epoch) + 1u;
        const uint32_t xres = __ldg(reinterpret_cast<const uint32_t*>(p.x) + (bh >> 3) * 256 + j * 32 + lane);
        if (lane == 0) {
            mbar_init(bars + BAR_Q * 8, 1);
            mbar_init(bars + BAR_ST * 8, 1);
            mbar_init(bars + BAR_PO * 8, 1);
            mbar_init(bars + BAR_O * 8, 1);
            asm volatile("fence.mbarrier_init.release.cluster;" ::: "memory");
            mbar_expect_tx(bars + BAR_Q * 8, 1024);
            mbar_expect_tx(bars + BAR_ST * 8, 256);
            mbar_expect_tx(bars + BAR_PO * 8, 2048);
            mbar_expect_tx(bars + BAR_O * 8, 1024);
#pragma unroll
            for (int k = 0; k < NEMPTY; k++) mbar_init(bars + (BAR_EMPTY + k) * 8, (k >= CH_K && k < CH_V) ? 1 : NCW);
        }
        __syncwarp();
        asm volatile("barrier.cluster.arrive.relaxed.aligned;" ::: "memory");
        if (lane == 0) sts_u1(sb + SM_EPOCH, tag);
        __syncwarp();
        bar_arrive(1, NTHREADS);
        TS(0);
        asm volatile("barrier.cluster.wait.acquire.aligned;" ::: "memory");
        bar_sync(4, NCT + 32);
        {
            float mx = lds_f1(sb + SM_MAX + lane * 4);
            float sm = lds_f1(sb + SM_SUM + lane * 4);
#pragma unroll
            for (int o = 4; o < 32; o <<= 1) { mx = fmaxf(mx, __shfl_xor_sync(~0u, mx, o)); sm += __shfl_xor_sync(~0u, sm, o); }
            const uint32_t dst = mapa(sb + SM_INS + (j * 4 + (lane & 3)) * 8, lane >> 2);
            const uint32_t rbar = mapa(bars + BAR_ST * 8, lane >> 2);
            asm volatile("st.async.weak.shared::cluster.mbarrier::complete_tx::bytes.v2.f32 [%0], {%1, %2}, [%3];"
                         ::"r"(dst), "f"(mx), "f"(sm), "r"(rbar) : "memory");
        }
        TS(2);
        float coef[8];
        {
            mbar_wait_cluster(bars + BAR_ST * 8);
            const float2 st = lds_f2(sb + SM_INS + lane * 8);
            float gm = st.x;
#pragma unroll
            for (int o = 4; o < 32; o <<= 1) gm = fmaxf(gm, __shfl_xor_sync(~0u, gm, o));
            const float wj = ex2((st.x - gm) * LOG2E);
            float gl = wj * st.y;
#pragma unroll
            for (int o = 4; o < 32; o <<= 1) gl += __shfl_xor_sync(~0u, gl, o);
            const float cj = wj / gl;
#pragma unroll
            for (int k = 0; k < 8; k++) coef[k] = __shfl_sync(~0u, cj, k * 4 + (lane >> 3));
        }
        TS(3);
        mbar_wait_cluster(bars + BAR_PO * 8);
        {
            float o0 = 0.f, o1 = 0.f;
#pragma unroll
            for (int k = 0; k < 8; k++) {
                const float2 v = lds_f2(sb + SM_INB + k * 256 + lane * 8);
                o0 = fmaf(coef[k], v.x, o0);
                o1 = fmaf(coef[k], v.y, o1);
            }
            const uint32_t op = pack_bf16(o0, o1);
            const int t = (lane >> 1) & 3, q = (lane >> 3) * 2 + (j >> 2);
            const uint32_t dst = sb + SM_O + (((j >> 1) & 1) * 4 + t) * 128 + ((q ^ (2 * t)) << 4) + ((j & 1) * 2 + (lane & 1)) * 4;
#pragma unroll
            for (int k = 0; k < 8; k++)
                asm volatile("st.async.weak.shared::cluster.mbarrier::complete_tx::bytes.u32 [%0], %1, [%2];"
                             ::"r"(mapa(dst, k)), "r"(op), "r"(mapa(bars + BAR_O * 8, k)) : "memory");
        }
        TS(4);
        if ((bh & 7) != 0) return;
        float2 s = make_float2(bf_lo(xres), bf_hi(xres));
#pragma unroll
        for (int part = 0; part < 2; part++) {
            const unsigned long long* src = part == 0 ? &sc->pf[((2 * j + (lane >> 4)) * 8) * 64 + (bh >> 3) * 32 + (lane & 15) * 2]
                                                      : &sc->pa[(((bh >> 3) * 8 + j) * 8) * 64 + lane * 2];
            unsigned long long v[8][2] = {};
            unsigned n = 0;
            while (true) {
#pragma unroll
                for (int i = 0; i < 8; i++)
                    if (!tag_ok(v[i][0], v[i][1], tag)) ld_ll2(src + i * 64, v[i][0], v[i][1]);
                bool ok = true;
#pragma unroll
                for (int i = 0; i < 8; i++) ok = ok && tag_ok(v[i][0], v[i][1], tag);
                if (ok || ++n >= SPIN_LIMIT) break;
            }
#pragma unroll
            for (int i = 0; i < 8; i++) { s.x += __uint_as_float((uint32_t)v[i][0]); s.y += __uint_as_float((uint32_t)v[i][1]); }
        }
        reinterpret_cast<uint32_t*>(p.out)[(bh >> 3) * 256 + j * 32 + lane] = pack_bf16(s.x, s.y);
        __syncwarp();
        if (c == 0 && lane == 0) sc->epoch = tag;
        TS(16);
        return;
    }

    const int u = warp;
    const int fg = lane >> 2, ft = lane & 3;
    asm volatile("barrier.cluster.arrive.relaxed.aligned;" ::: "memory");

    uint32_t b1pair = 0;
    if (u < 2) {
        const uint4* x4 = reinterpret_cast<const uint4*>(p.x) + u * 64 + lane * 2;
        const uint4 v0 = __ldg(x4), v1 = __ldg(x4 + 1);
        if (u == 1 && c < 112) b1pair = __ldg(reinterpret_cast<const uint32_t*>(p.b1) + c * 8 + (lane & 7));
        const uint32_t a[8] = {v0.x, v0.y, v0.z, v0.w, v1.x, v1.y, v1.z, v1.w};
        float s0 = 0.f;
#pragma unroll
        for (int i = 0; i < 8; i++) s0 += bf_lo(a[i]) + bf_hi(a[i]);
#pragma unroll
        for (int o = 16; o > 0; o >>= 1) s0 += __shfl_xor_sync(~0u, s0, o);
        const float m0 = s0 * (1.f / D_MODEL);
        float q0 = 0.f;
#pragma unroll
        for (int i = 0; i < 8; i++) {
            float d;
            d = bf_lo(a[i]) - m0; q0 += d * d; d = bf_hi(a[i]) - m0; q0 += d * d;
        }
#pragma unroll
        for (int o = 16; o > 0; o >>= 1) q0 += __shfl_xor_sync(~0u, q0, o);
        const float mean = bf16r(m0);
        const float var = bf16r(q0 * (1.f / D_MODEL));
        const float den = bf16r(sqrtf(bf16r(var + 1e-5f)));
        const float rden = 1.f / den;
        uint32_t o[8];
#pragma unroll
        for (int i = 0; i < 8; i++) o[i] = pack_bf16(bf16r(bf_lo(a[i]) - mean) * rden, bf16r(bf_hi(a[i]) - mean) * rden);
        const uint32_t dst = sb + SM_XN + u * 1024 + lane * 32;
        sts_u4(dst, o[0], o[1], o[2], o[3]);
        sts_u4(dst + 16, o[4], o[5], o[6], o[7]);
        TS(0);
    }

    const int lrow = (lane & 7) + ((lane >> 4) << 3);
    const int lchk = (lane >> 3) & 1;

    bar_sync(1, NTHREADS);
    const uint32_t tag = lds_u1(sb + SM_EPOCH);

    const uint32_t wa512 = sb + ((u >> 2) * 32 + lrow) * 128 + ((((u & 3) * 2 + lchk) ^ (lrow & 7)) << 4);
    const uint32_t red512 = sb + SM_REDA + ((u >> 2) * 64 + (u & 3) * 16 + fg) * 4;

    {
        uint32_t bb[8][4];
        const uint32_t xa = sb + SM_XN + (bh >> 3) * 1024 + ((u >> 2) * 16 + ft) * 4;
#pragma unroll
        for (int q = 0; q < 8; q++)
#pragma unroll
            for (int i = 0; i < 4; i++) bb[q][i] = lds_u1(xa + q * 128 + i * 16);
        gemv512<CH_WQ, true>(bb, wa512, bars, red512, lane);
    }
    TS(1);
    asm volatile("barrier.cluster.wait.acquire.aligned;" ::: "memory");
    bar_sync(2, NCT);
    if (u == 0) {
        const float2 s0 = lds_f2(sb + SM_REDA + lane * 8), s1 = lds_f2(sb + SM_REDA + 256 + lane * 8);
        const uint32_t qp = pack_bf16(s0.x + s1.x, s0.y + s1.y);
        const uint32_t dst = sb + SM_Q + (((j >> 1) * 4 + (lane & 3)) * 16 + (j & 1) * 8 + (lane >> 2)) * 4;
#pragma unroll
        for (int k = 0; k < 8; k++)
            asm volatile("st.async.weak.shared::cluster.mbarrier::complete_tx::bytes.u32 [%0], %1, [%2];"
                         ::"r"(mapa(dst, k)), "r"(qp), "r"(mapa(bars + BAR_Q * 8, k)) : "memory");
        TS(2);
    }

    if (c < 112) {
        uint32_t xb[4][2];
#pragma unroll
        for (int q = 0; q < 4; q++) {
            xb[q][0] = lds_u1(sb + SM_XN + (fg & 1) * 1024 + (q * 64 + u * 8 + ft) * 4);
            xb[q][1] = lds_u1(sb + SM_XN + (fg & 1) * 1024 + (q * 64 + u * 8 + 4 + ft) * 4);
        }
        float acc[4] = {};
#pragma unroll
        for (int q = 0; q < 4; q++) {
            if ((q & 1) == 0) mbar_wait(bars + (CH_W1 + (q >> 1)) * 8);
            const int row = (q & 1) * 128 + u * 16 + lrow;
            uint32_t a[4];
            ldsm4t(a, sb + slot_off(CH_W1 + (q >> 1)) + row * 32 + ((lchk ^ ((row >> 2) & 1)) << 4));
            mma16816(acc, a[0], a[1], a[2], a[3], xb[q][0], xb[q][1]);
            if ((q & 1) && lane == 0) mbar_arrive(bars + (BAR_EMPTY + CH_W1 + (q >> 1)) * 8);
        }
        TS(10);
        if (ft == 0) {
            const uint32_t rb = sb + SM_REDB + u * 128;
            sts_f1(rb + fg * 4, acc[0]);
            sts_f1(rb + 64 + fg * 4, acc[1]);
            sts_f1(rb + (fg + 8) * 4, acc[2]);
            sts_f1(rb + 64 + (fg + 8) * 4, acc[3]);
        }
        bar_sync(2, NCT);
        if (u == 1 && lane < 16) {
            float2 s = make_float2(0.f, 0.f);
#pragma unroll
            for (int k = 0; k < NCW; k++) {
                float2 v = lds_f2(sb + SM_REDB + k * 128 + lane * 8);
                s.x += v.x; s.y += v.y;
            }
            float h[2] = {bf16r(bf16r(s.x) + bf_lo(b1pair)), bf16r(bf16r(s.y) + bf_hi(b1pair))};
            float a[2];
#pragma unroll
            for (int i = 0; i < 2; i++) {
                const float e = bf16r(__expf(-fabsf(h[i])));
                const float sp = bf16r(bf16r(log1pf(e)) + fmaxf(h[i], 0.f));
                a[i] = h[i] * bf16r(tanhf(sp));
            }
            const int dp = lane & 7;
            st_ll1(&sc->ax[(((lane >> 3) * 112 + c) * 4 + (dp & 3)) * 2 + (dp >> 2)], pack_bf16(a[0], a[1]), tag);
            TS(7);
        }
    } else if (lane == 0) {
        mbar_arrive(bars + (BAR_EMPTY + CH_W1) * 8);
        mbar_arrive(bars + (BAR_EMPTY + CH_W1 + 1) * 8);
    }
    __syncwarp();

    {
        mbar_wait_cluster(bars + BAR_Q * 8);
        TS(3);
        uint32_t qa[16];
#pragma unroll
        for (int i = 0; i < 4; i++) lds_u4(qa + 4 * i, sb + SM_Q + ((fg & 3) * 4 + ft) * 64 + i * 16);
        mbar_wait(bars + (CH_K + u) * 8);
        TS(4);
        float acc[4][4] = {};
        const uint32_t kb = sb + ((CH_K + u) % NSLOT) * 8192 + (lane & 7) * 128;
#pragma unroll
        for (int q = 0; q < 4; q++) {
            const int chunk = q * 4 + (lane >> 3);
            const uint32_t off = (chunk >> 3) * 4096 + (((chunk & 7) ^ (lane & 7)) << 4);
#pragma unroll
            for (int nt = 0; nt < 4; nt++) {
                uint32_t b[4];
                ldsm4(b, kb + nt * 1024 + off);
                mma16816(acc[nt], qa[4 * q], 0u, qa[4 * q + 1], 0u, b[0], b[1]);
                mma16816(acc[nt], qa[4 * q + 2], 0u, qa[4 * q + 3], 0u, b[2], b[3]);
            }
        }
        if (lane == 0) mbar_arrive(bars + (BAR_EMPTY + CH_K + u) * 8);
        const float scale = 0.08838834764831845f;
        float sv[8];
#pragma unroll
        for (int i = 0; i < 8; i++) sv[i] = bf16r(bf16r(acc[i >> 1][i & 1]) * scale);
        float m = fmaxf(fmaxf(fmaxf(sv[0], sv[1]), fmaxf(sv[2], sv[3])), fmaxf(fmaxf(sv[4], sv[5]), fmaxf(sv[6], sv[7])));
        m = fmaxf(m, __shfl_xor_sync(~0u, m, 1));
        m = fmaxf(m, __shfl_xor_sync(~0u, m, 2));
        if (lane < 16 && ft == 0) sts_f1(sb + SM_MAX + (u * 4 + fg) * 4, m);
        TS(5);
        bar_sync(2, NCT);
        m = lds_f1(sb + SM_MAX + ((ft + 4 * (fg >> 2)) * 4 + (fg & 3)) * 4);
        m = fmaxf(m, __shfl_xor_sync(~0u, m, 1));
        m = fmaxf(m, __shfl_xor_sync(~0u, m, 2));
        m = fmaxf(m, __shfl_xor_sync(~0u, m, 16));
#pragma unroll
        for (int i = 0; i < 8; i++) sv[i] = ex2((sv[i] - m) * LOG2E);
        float l = ((sv[0] + sv[1]) + (sv[2] + sv[3])) + ((sv[4] + sv[5]) + (sv[6] + sv[7]));
        l += __shfl_xor_sync(~0u, l, 1);
        l += __shfl_xor_sync(~0u, l, 2);
        if (lane < 16) {
            sts_u4(sb + SM_P + (u * 16 + lane) * 16, pack_bf16(sv[0], sv[1]), pack_bf16(sv[2], sv[3]), pack_bf16(sv[4], sv[5]),
                   pack_bf16(sv[6], sv[7]));
            if (ft == 0) sts_f1(sb + SM_SUM + (u * 4 + fg) * 4, l);
        }
        bar_sync(4, NCT + 32);
        TS(6);
    }

    unsigned long long w[2][2] = {};
    const unsigned long long* sa = &sc->ax[(((fg & 1) * 112 + r * 14 + (u < 7 ? u : 0)) * 4 + ft) * 2];
    if (lane < 8) {
        ld_ll2(sa, w[0][0], w[0][1]);
        ld_ll2(sa + 56, w[1][0], w[1][1]);
    }
    {
        float acc[2][4] = {};
        const uint32_t voff = (u >> 2) * 4096 + lane * 128;
        const uint32_t c0 = (((u & 3) * 2) ^ (lane & 7)) << 4, c1 = (((u & 3) * 2 + 1) ^ (lane & 7)) << 4;
#pragma unroll
        for (int i = 0; i < 8; i++) {
            uint32_t pa[4], b0[4], b1[4];
            lds_u4(pa, sb + SM_P + (i * 16 + (lane & 15)) * 16);
            mbar_wait(bars + (CH_V + i) * 8);
            ldsm4t(b0, sb + slot_off(CH_V + i) + voff + c0);
            ldsm4t(b1, sb + slot_off(CH_V + i) + voff + c1);
            mma16816(acc[0], pa[0], 0u, pa[1], 0u, b0[0], b0[1]);
            mma16816(acc[1], pa[0], 0u, pa[1], 0u, b1[0], b1[1]);
            mma16816(acc[0], pa[2], 0u, pa[3], 0u, b0[2], b0[3]);
            mma16816(acc[1], pa[2], 0u, pa[3], 0u, b1[2], b1[3]);
            if (CH_V + i < NEMPTY && lane == 0) mbar_arrive(bars + (BAR_EMPTY + CH_V + i) * 8);
        }
        TS(8);
        if (lane < 16) {
            const uint32_t dst = mapa(sb + SM_INB + j * 256 + lane * 16, u);
            const uint32_t rbar = mapa(bars + BAR_PO * 8, u);
            asm volatile("st.async.weak.shared::cluster.mbarrier::complete_tx::bytes.v4.f32 [%0], {%1, %2, %3, %4}, [%5];"
                         ::"r"(dst), "f"(acc[0][0]), "f"(acc[0][1]), "f"(acc[1][0]), "f"(acc[1][1]), "r"(rbar) : "memory");
        }
        TS(9);
    }

    {
        if (lane < 8) {
            unsigned n = 0;
            while (!(tag_ok(w[0][0], w[0][1], tag) && tag_ok(w[1][0], w[1][1], tag)) && ++n < SPIN_LIMIT) {
                ld_ll2(sa, w[0][0], w[0][1]);
                ld_ll2(sa + 56, w[1][0], w[1][1]);
            }
        }
        __syncwarp();
        if (u < 7) {
            float acc[2][4] = {}, acc2[2][4] = {};
            mbar_wait_n(bars + CH_W2 * 8, 2, lane);
            gemv_tile64(acc, sb + slot_off(CH_W2), u * 16 + lrow, lchk, (uint32_t)w[0][0], (uint32_t)w[0][1]);
            gemv_tile64(acc2, sb + slot_off(CH_W2 + 1), u * 16 + lrow, lchk, (uint32_t)w[1][0], (uint32_t)w[1][1]);
#pragma unroll
            for (int mt = 0; mt < 2; mt++)
#pragma unroll
                for (int i = 0; i < 4; i++) acc[mt][i] += acc2[mt][i];
            if (ft == 0) {
                const uint32_t rb = sb + SM_REDG + u * 256;
#pragma unroll
                for (int mt = 0; mt < 2; mt++) {
                    sts_f1(rb + (mt * 16 + fg) * 4, acc[mt][0]);
                    sts_f1(rb + 128 + (mt * 16 + fg) * 4, acc[mt][1]);
                    sts_f1(rb + (mt * 16 + fg + 8) * 4, acc[mt][2]);
                    sts_f1(rb + 128 + (mt * 16 + fg + 8) * 4, acc[mt][3]);
                }
            }
            bar_arrive(3, NCT);
        } else {
            bar_sync(3, NCT);
            float2 s = make_float2(0.f, 0.f);
#pragma unroll
            for (int k = 0; k < 7; k++) {
                const float2 t = lds_f2(sb + SM_REDG + k * 256 + lane * 8);
                s.x += t.x; s.y += t.y;
            }
            st_ll2(&sc->pf[(g16 * 8 + r) * 64 + lane * 2], __float_as_uint(s.x), __float_as_uint(s.y), tag);
        }
        TS(11);
    }

    mbar_wait_cluster(bars + BAR_O * 8);
    TS(12);
    {
        uint32_t bb[8][4];
#pragma unroll
        for (int q = 0; q < 8; q++) lds_u4(bb[q], sb + SM_O + ((u >> 2) * 4 + ft) * 128 + ((q ^ (2 * ft)) << 4));
        gemv512<CH_WO, false>(bb, wa512, bars, red512, lane);
    }
    TS(14);
    if (u != 0) { bar_arrive(2, NCT); return; }
    bar_sync(2, NCT);
    {
        const float2 s0 = lds_f2(sb + SM_REDA + lane * 8), s1 = lds_f2(sb + SM_REDA + 256 + lane * 8);
        st_ll2(&sc->pa[((((bh >> 3) * 8 + j) * 8) + (bh & 7)) * 64 + lane * 2], __float_as_uint(s0.x + s1.x),
               __float_as_uint(s0.y + s1.y), tag);
        TS(15);
    }
}

typedef CUresult (*EncodeTiledFn)(CUtensorMap*, CUtensorMapDataType, cuuint32_t, void*, const cuuint64_t*, const cuuint64_t*,
                                  const cuuint32_t*, const cuuint32_t*, CUtensorMapInterleave, CUtensorMapSwizzle,
                                  CUtensorMapL2promotion, CUtensorMapFloatOOBfill);

void make_map(EncodeTiledFn enc, CUtensorMap* m, const void* base, uint64_t cols, uint64_t rows, uint32_t box_c, uint32_t box_r,
              CUtensorMapSwizzle sw) {
    cuuint64_t gd[2] = {cols, rows};
    cuuint64_t gs[1] = {cols * 2};
    cuuint32_t bd[2] = {box_c, box_r};
    cuuint32_t es[2] = {1, 1};
    enc(m, CU_TENSOR_MAP_DATA_TYPE_BFLOAT16, 2, const_cast<void*>(base), gd, gs, bd, es, CU_TENSOR_MAP_INTERLEAVE_NONE, sw,
        CU_TENSOR_MAP_L2_PROMOTION_L2_128B, CU_TENSOR_MAP_FLOAT_OOB_FILL_NONE);
}

}

extern "C" void kernel_launch(void* const* d_in, const int* in_sizes, int n_in, void* d_out, int out_size) {
    (void)in_sizes; (void)n_in; (void)out_size;
    static EncodeTiledFn enc = nullptr;
    static Scratch* sc = nullptr;
    if (!enc) {
        void* fn = nullptr;
        cudaDriverEntryPointQueryResult st;
        cudaGetDriverEntryPoint("cuTensorMapEncodeTiled", &fn, cudaEnableDefault, &st);
        enc = (EncodeTiledFn)fn;
        cudaFuncSetAttribute(fused_decode_kernel, cudaFuncAttributeMaxDynamicSharedMemorySize, SM_TOTAL);
        void* sp = nullptr;
        cudaGetSymbolAddress(&sp, g_scratch);
        sc = (Scratch*)sp;
    }
    Params p;
    make_map(enc, &p.k, d_in[1], 128, 2 * 8 * SK, 64, 32, CU_TENSOR_MAP_SWIZZLE_128B);
    make_map(enc, &p.v, d_in[2], 128, 2 * 8 * SK, 64, 32, CU_TENSOR_MAP_SWIZZLE_128B);
    make_map(enc, &p.wq, d_in[3], 4096, 512, 64, 64, CU_TENSOR_MAP_SWIZZLE_128B);
    make_map(enc, &p.wo, d_in[4], 512, 4096, 64, 64, CU_TENSOR_MAP_SWIZZLE_128B);
    make_map(enc, &p.w1, d_in[6], FF, 512, 16, 256, CU_TENSOR_MAP_SWIZZLE_32B);
    make_map(enc, &p.w2, d_in[8], 512, FF, 32, 112, CU_TENSOR_MAP_SWIZZLE_64B);
    p.x = (const __nv_bfloat16*)d_in[0];
    p.b1 = (const __nv_bfloat16*)d_in[7];
    p.out = (__nv_bfloat16*)d_out;
    p.sc = sc;
    fused_decode_kernel<<<NCTA, NTHREADS, SM_TOTAL, cudaStreamPerThread>>>(p);
}
```

```cpp
#include <cuda_runtime.h>
#include <cuda_bf16.h>
#include <cuda.h>
#include <stdint.h>

namespace {

constexpr int D_MODEL = 512;
constexpr int SK = 8192;
constexpr int WIN = 2048;
constexpr int WIN0 = SK - WIN;
constexpr int FF = 1792;

constexpr int NCTA = 64;
constexpr int NCW = 8;
constexpr int NCT = NCW * 32;
constexpr int NTHREADS = (NCW + 2) * 32;

constexpr int CH_WQ = 0, CH_W1 = 8, CH_K = 12, CH_V = 28, CH_WO = 44, CH_W2 = 52, NCHUNK = 56;
constexpr int CH_POSTV = CH_V + 16;
constexpr int NSLOT = 26;
constexpr int NEMPTY = NCHUNK - NSLOT;
constexpr int WINDOW = 14;
constexpr int WINDOW2 = 9;
constexpr int WINDOW3 = 6;
__host__ __device__ constexpr int slot_off(int chunk) { return (chunk % NSLOT) * 8192; }

constexpr int BAR_EMPTY = NCHUNK;
constexpr int BAR_Q = BAR_EMPTY + NEMPTY;
constexpr int BAR_A = BAR_Q + 1;
constexpr int BAR_ST = BAR_A + 1;
constexpr int BAR_PO = BAR_ST + 1;
constexpr int BAR_O = BAR_PO + 1;
constexpr int BAR_F = BAR_O + 1;
constexpr int BAR_ACK = BAR_F + 1;
constexpr int NBAR = BAR_ACK + 1;

constexpr int SM_INB = NSLOT * 8192;
constexpr int SM_O = SM_INB + 2048;
constexpr int SM_A = SM_O + 2048;
constexpr int SM_Q = SM_A + 1024;
constexpr int SM_P = SM_Q + 1024;
constexpr int SM_INF = SM_P;
constexpr int SM_XN = SM_P + 4096;
constexpr int SM_REDA = SM_XN + 2048;
constexpr int SM_REDB = SM_REDA + 1024;
constexpr int SM_INS = SM_REDB + 2048;
constexpr int SM_MAX = SM_INS + 128;
constexpr int SM_SUM = SM_MAX + 128;
constexpr int SM_BAR = SM_SUM + 128;
constexpr int SM_EPOCH = SM_BAR + NBAR * 8;
constexpr int SM_TOTAL = SM_EPOCH + 8;
static_assert(SM_TOTAL <= 232448, "shared memory");

constexpr int NPRE = 6;
constexpr unsigned SPIN_LIMIT = 1u << 20;

struct __align__(128) Scratch {
    unsigned epoch;
    unsigned pad[31];
    unsigned long long ax[8 * 2 * 128];
    unsigned long long pa[2 * 8 * 8 * 64];
};

__device__ Scratch g_scratch;

struct Params {
    CUtensorMap wq, k, v, w1, wo, w2;
    const __nv_bfloat16* x;
    const __nv_bfloat16* b1;
    __nv_bfloat16* out;
    Scratch* sc;
};

__device__ __forceinline__ uint32_t smem_u32(const void* p) { return (uint32_t)__cvta_generic_to_shared(p); }
__device__ __forceinline__ void mbar_init(uint32_t bar, uint32_t cnt) {
    asm volatile("mbarrier.init.shared::cta.b64 [%0], %1;" ::"r"(bar), "r"(cnt) : "memory");
}
__device__ __forceinline__ void mbar_expect_tx(uint32_t bar, uint32_t bytes) {
    asm volatile("mbarrier.arrive.expect_tx.shared::cta.b64 _, [%0], %1;" ::"r"(bar), "r"(bytes) : "memory");
}
__device__ __forceinline__ void mbar_arrive(uint32_t bar) {
    asm volatile("mbarrier.arrive.shared::cta.b64 _, [%0];" ::"r"(bar) : "memory");
}
__device__ __forceinline__ void mbar_wait(uint32_t bar) {
    unsigned n = 0;
    uint32_t ok;
    do {
        asm volatile("{\n.reg .pred p;\nmbarrier.try_wait.parity.shared::cta.b64 p, [%1], 0;\nselp.u32 %0, 1, 0, p;\n}"
                     : "=r"(ok) : "r"(bar) : "memory");
    } while (!ok && ++n < SPIN_LIMIT);
}
__device__ __forceinline__ void mbar_wait_cluster(uint32_t bar) {
    unsigned n = 0;
    uint32_t ok;
    do {
        asm volatile("{\n.reg .pred p;\nmbarrier.try_wait.parity.acquire.cluster.shared::cta.b64 p, [%1], 0;\nselp.u32 %0, 1, 0, p;\n}"
                     : "=r"(ok) : "r"(bar) : "memory");
    } while (!ok && ++n < SPIN_LIMIT);
}
__device__ __forceinline__ void tma2d(uint32_t dst, const CUtensorMap* tm, int c0, int c1, uint32_t bar) {
    asm volatile("cp.async.bulk.tensor.2d.shared::cluster.global.mbarrier::complete_tx::bytes [%0], [%1, {%3, %4}], [%2];"
                 ::"r"(dst), "l"((uint64_t)tm), "r"(bar), "r"(c0), "r"(c1) : "memory");
}
__device__ __forceinline__ uint32_t mapa(uint32_t addr, uint32_t rank) {
    uint32_t r;
    asm("mapa.shared::cluster.u32 %0, %1, %2;" : "=r"(r) : "r"(addr), "r"(rank));
    return r;
}
__device__ __forceinline__ void bar_sync(int id, int n) { asm volatile("bar.sync %0, %1;" ::"r"(id), "r"(n) : "memory"); }
__device__ __forceinline__ void bar_arrive(int id, int n) { asm volatile("bar.arrive %0, %1;" ::"r"(id), "r"(n) : "memory"); }

__device__ __forceinline__ void ldsm4(uint32_t (&r)[4], uint32_t addr) {
    asm volatile("ldmatrix.sync.aligned.m8n8.x4.shared.b16 {%0,%1,%2,%3}, [%4];"
                 : "=r"(r[0]), "=r"(r[1]), "=r"(r[2]), "=r"(r[3]) : "r"(addr) : "memory");
}
__device__ __forceinline__ void ldsm4t(uint32_t (&r)[4], uint32_t addr) {
    asm volatile("ldmatrix.sync.aligned.m8n8.x4.trans.shared.b16 {%0,%1,%2,%3}, [%4];"
                 : "=r"(r[0]), "=r"(r[1]), "=r"(r[2]), "=r"(r[3]) : "r"(addr) : "memory");
}
__device__ __forceinline__ void mma16816(float (&c)[4], uint32_t a0, uint32_t a1, uint32_t a2, uint32_t a3, uint32_t b0, uint32_t b1) {
    asm volatile("mma.sync.aligned.m16n8k16.row.col.f32.bf16.bf16.f32 {%0,%1,%2,%3}, {%4,%5,%6,%7}, {%8,%9}, {%0,%1,%2,%3};"
                 : "+f"(c[0]), "+f"(c[1]), "+f"(c[2]), "+f"(c[3])
                 : "r"(a0), "r"(a1), "r"(a2), "r"(a3), "r"(b0), "r"(b1));
}
__device__ __forceinline__ void st_ll1(unsigned long long* p, uint32_t d, uint32_t tag) {
    unsigned long long w = ((unsigned long long)tag << 32) | d;
    asm volatile("st.relaxed.gpu.global.b64 [%0], %1;" ::"l"(p), "l"(w) : "memory");
}
__device__ __forceinline__ void st_ll2(unsigned long long* p, uint32_t d0, uint32_t d1, uint32_t tag) {
    unsigned long long w0 = ((unsigned long long)tag << 32) | d0, w1 = ((unsigned long long)tag << 32) | d1;
    asm volatile("st.relaxed.gpu.global.v2.b64 [%0], {%1, %2};" ::"l"(p), "l"(w0), "l"(w1) : "memory");
}
__device__ __forceinline__ void ld_ll2(const unsigned long long* p, unsigned long long& w0, unsigned long long& w1) {
    asm volatile("ld.relaxed.gpu.global.v2.b64 {%0, %1}, [%2];" : "=l"(w0), "=l"(w1) : "l"(p) : "memory");
}
__device__ __forceinline__ bool tag_ok(unsigned long long w0, unsigned long long w1, uint32_t tag) {
    return (uint32_t)(w0 >> 32) == tag && (uint32_t)(w1 >> 32) == tag;
}
__device__ __forceinline__ float ex2(float x) {
    float y;
    asm("ex2.approx.ftz.f32 %0, %1;" : "=f"(y) : "f"(x));
    return y;
}
__device__ __forceinline__ float bf16r(float x) { return __bfloat162float(__float2bfloat16_rn(x)); }
__device__ __forceinline__ uint32_t pack_bf16(float lo, float hi) {
    __nv_bfloat162 v = __floats2bfloat162_rn(lo, hi);
    return *reinterpret_cast<uint32_t*>(&v);
}
__device__ __forceinline__ float bf_lo(uint32_t u) { return __uint_as_float(u << 16); }
__device__ __forceinline__ float bf_hi(uint32_t u) { return __uint_as_float(u & 0xffff0000u); }
__device__ __forceinline__ float2 lds_f2(uint32_t a) {
    float2 v;
    asm volatile("ld.shared.v2.f32 {%0, %1}, [%2];" : "=f"(v.x), "=f"(v.y) : "r"(a) : "memory");
    return v;
}
__device__ __forceinline__ float lds_f1(uint32_t a) {
    float v;
    asm volatile("ld.shared.f32 %0, [%1];" : "=f"(v) : "r"(a) : "memory");
    return v;
}
__device__ __forceinline__ uint32_t lds_u1(uint32_t a) {
    uint32_t v;
    asm volatile("ld.shared.u32 %0, [%1];" : "=r"(v) : "r"(a) : "memory");
    return v;
}
__device__ __forceinline__ void lds_u4(uint32_t* r, uint32_t a) {
    asm volatile("ld.shared.v4.u32 {%0,%1,%2,%3}, [%4];" : "=r"(r[0]), "=r"(r[1]), "=r"(r[2]), "=r"(r[3]) : "r"(a) : "memory");
}
__device__ __forceinline__ float4 lds_f4(uint32_t a) {
    float4 v;
    asm volatile("ld.shared.v4.f32 {%0,%1,%2,%3}, [%4];" : "=f"(v.x), "=f"(v.y), "=f"(v.z), "=f"(v.w) : "r"(a) : "memory");
    return v;
}
__device__ __forceinline__ void sts_f1(uint32_t a, float v) { asm volatile("st.shared.f32 [%0], %1;" ::"r"(a), "f"(v) : "memory"); }
__device__ __forceinline__ void sts_u1(uint32_t a, uint32_t v) { asm volatile("st.shared.u32 [%0], %1;" ::"r"(a), "r"(v) : "memory"); }
__device__ __forceinline__ void sts_u4(uint32_t a, uint32_t x, uint32_t y, uint32_t z, uint32_t w) {
    asm volatile("st.shared.v4.u32 [%0], {%1,%2,%3,%4};" ::"r"(a), "r"(x), "r"(y), "r"(z), "r"(w) : "memory");
}

__device__ __forceinline__ void gemv_tile64(float (&acc)[2][4], uint32_t base, int row, int lchk, uint32_t b0, uint32_t b1) {
    uint32_t a0[4], a1[4];
    const uint32_t ra = base + row * 64;
    const int sw = (row >> 1) & 3;
    ldsm4t(a0, ra + ((lchk ^ sw) << 4));
    ldsm4t(a1, ra + (((2 + lchk) ^ sw) << 4));
    mma16816(acc[0], a0[0], a0[1], a0[2], a0[3], b0, b1);
    mma16816(acc[1], a1[0], a1[1], a1[2], a1[3], b0, b1);
}

__device__ __forceinline__ void st_async_u32(uint32_t dst, uint32_t v, uint32_t bar, uint32_t rank) {
    asm volatile("st.async.weak.shared::cluster.mbarrier::complete_tx::bytes.u32 [%0], %1, [%2];"
                 ::"r"(mapa(dst, rank)), "r"(v), "r"(mapa(bar, rank)) : "memory");
}
__device__ __forceinline__ void st_async_u32x2(uint32_t dst, uint32_t v0, uint32_t v1, uint32_t bar, uint32_t rank) {
    asm volatile("st.async.weak.shared::cluster.mbarrier::complete_tx::bytes.v2.u32 [%0], {%1, %2}, [%3];"
                 ::"r"(mapa(dst, rank)), "r"(v0), "r"(v1), "r"(mapa(bar, rank)) : "memory");
}

template <int CH0, bool RELEASE, int N, int NB>
__device__ __forceinline__ void gemv_chunks(float (&acc)[4], float (&acc2)[4], const uint32_t (&bb)[NB][4], uint32_t wa, uint32_t bars,
                                            int lane) {
    uint32_t a0[2][4], a1[2][4];
#pragma unroll
    for (int q = 0; q <= N; q++) {
        if (q < N) {
            mbar_wait(bars + (CH0 + q) * 8);
            ldsm4t(a0[q & 1], wa + slot_off(CH0 + q));
            ldsm4t(a1[q & 1], wa + slot_off(CH0 + q) + 2048);
        }
        if (q > 0) {
            const int k = (q - 1) & 1;
            mma16816(acc, a0[k][0], a0[k][1], a0[k][2], a0[k][3], bb[q - 1][0], bb[q - 1][1]);
            mma16816(acc2, a1[k][0], a1[k][1], a1[k][2], a1[k][3], bb[q - 1][2], bb[q - 1][3]);
            if (RELEASE && lane == 0) mbar_arrive(bars + (BAR_EMPTY + CH0 + q - 1) * 8);
        }
    }
}

__global__ void __cluster_dims__(8, 1, 1) __launch_bounds__(NTHREADS, 1) fused_decode_kernel(const __grid_constant__ Params p) {
    extern __shared__ __align__(1024) uint8_t smem[];
    const uint32_t sb = smem_u32(smem);
    const uint32_t bars = sb + SM_BAR;
    const int c = blockIdx.x;
    const int warp = threadIdx.x >> 5, lane = threadIdx.x & 31;
    const int hkv = c >> 3, rk = c & 7;
    const int b = rk >> 2, sp = rk & 3;

    if (warp < NCW && lane == 0)
        asm volatile("cp.async.bulk.prefetch.tensor.2d.L2.global [%0, {%1, %2}];" ::"l"((uint64_t)&p.wq), "r"(64 * c), "r"(64 * warp) : "memory");
    if (warp == NCW) {
        if (lane == 0) {
#pragma unroll
            for (int i = 0; i < 8; i++) mbar_init(bars + i * 8, 1);
            asm volatile("fence.proxy.async.shared::cta;" ::: "memory");
#pragma unroll
            for (int i = 0; i < 8; i++) {
                mbar_expect_tx(bars + i * 8, 8192);
                tma2d(sb + slot_off(i), &p.wq, 64 * c, 64 * i, bars + i * 8);
            }
        }
        __syncwarp();
        asm volatile("barrier.cluster.arrive.relaxed.aligned;" ::: "memory");
        if (lane == 0) {
#pragma unroll
            for (int k = 8; k < NCHUNK; k++) mbar_init(bars + k * 8, 1);
            asm volatile("fence.proxy.async.shared::cta;" ::: "memory");
        }
        __syncwarp();
        bar_arrive(1, NTHREADS);
        const int krow = (b * 8 + hkv) * SK + WIN0 + sp * 512;
        auto issue = [&](const int i) {
            const uint32_t bar = bars + i * 8;
            const uint32_t dst = sb + slot_off(i);
            if (i >= CH_W2) mbar_wait(bar - WINDOW3 * 8);
            else if (i >= CH_POSTV && i - WINDOW2 < CH_POSTV) mbar_wait(bar - WINDOW2 * 8);
            else if (i >= WINDOW) mbar_wait(bar - WINDOW * 8);
            if (i >= NSLOT) mbar_wait(bars + (BAR_EMPTY + i - NSLOT) * 8);
            if (i >= CH_W1 && i < CH_W1 + 4) {
                if (rk < 7) {
                    mbar_expect_tx(bar, 8192);
                    tma2d(dst, &p.w1, 224 * hkv + 32 * rk, 128 * (i - CH_W1), bar);
                } else {
                    mbar_expect_tx(bar, 0);
                }
            } else if (i >= CH_K && i < CH_K + 16) {
                mbar_expect_tx(bar, 8192);
                tma2d(dst, &p.k, 0, krow + (i - CH_K) * 32, bar);
                tma2d(dst + 4096, &p.k, 64, krow + (i - CH_K) * 32, bar);
            } else if (i >= CH_V && i < CH_V + 16) {
                mbar_expect_tx(bar, 8192);
                tma2d(dst, &p.v, 0, krow + (i - CH_V) * 32, bar);
                tma2d(dst + 4096, &p.v, 64, krow + (i - CH_V) * 32, bar);
            } else if (i >= CH_W2) {
                mbar_expect_tx(bar, i < NCHUNK - 1 ? 8192 : 4096);
                tma2d(dst, &p.w2, 64 * hkv, 224 * rk + 64 * (i - CH_W2), bar);
                if (i < NCHUNK - 1) tma2d(dst + 4096, &p.w2, 64 * hkv, 224 * rk + 64 * (i - CH_W2) + 32, bar);
            } else {
                mbar_expect_tx(bar, 8192);
                tma2d(dst, &p.wo, 64 * rk, 512 * hkv + 64 * (i - CH_WO), bar);
            }
        };
        if (lane == 0) {
#pragma unroll
            for (int i = 8; i < NSLOT; i++) issue(i);
        }
        __syncwarp();
        bar_sync(5, 64);
        if (lane == 0) {
#pragma unroll
            for (int i = NSLOT; i < NCHUNK; i++) issue(i);
        }
        return;
    }

    Scratch* const sc = p.sc;
    const float LOG2E = 1.4426950408889634f;

    if (warp == NCW + 1) {
        const uint32_t tag = *reinterpret_cast<volatile unsigned*>(&sc->epoch) + 1u;
        const uint32_t xres = __ldg(reinterpret_cast<const uint32_t*>(p.x) + (rk & 1) * 256 + hkv * 32 + lane);
        if (lane == 0) {
#pragma unroll
            for (int k = BAR_Q; k < NBAR; k++) mbar_init(bars + k * 8, k == BAR_ACK ? 2 : 1);
            asm volatile("fence.mbarrier_init.release.cluster;" ::: "memory");
        }
        __syncwarp();
        asm volatile("barrier.cluster.arrive.relaxed.aligned;" ::: "memory");
        if (lane == 0) {
            mbar_expect_tx(bars + BAR_Q * 8, 1024);
            mbar_expect_tx(bars + BAR_ST * 8, 128);
            mbar_expect_tx(bars + BAR_PO * 8, 2048);
            mbar_expect_tx(bars + BAR_O * 8, 2048);
            mbar_expect_tx(bars + BAR_F * 8, 4096);
#pragma unroll
            for (int k = 0; k < NEMPTY; k++) mbar_init(bars + (BAR_EMPTY + k) * 8, (k >= CH_K && k < CH_K + 16) ? 1 : NCW);
            sts_u1(sb + SM_EPOCH, tag);
        }
        __syncwarp();
        bar_arrive(5, 64);
        bar_sync(1, NTHREADS);
        asm volatile("barrier.cluster.wait.acquire.aligned;" ::: "memory");
        {
            mbar_wait(bars + (CH_K + 2) * 8);
            const unsigned long long* src = &sc->ax[rk * 256];
            unsigned pend = lane < 24 ? 0xfu : 0x5u, n = 0;
            while (true) {
                unsigned long long w[4][2];
#pragma unroll
                for (int k = 0; k < 4; k++)
                    if (pend >> k & 1) ld_ll2(src + (k >> 1) * 128 + ((k & 1) * 32 + lane) * 2, w[k][0], w[k][1]);
#pragma unroll
                for (int k = 0; k < 4; k++)
                    if ((pend >> k & 1) && tag_ok(w[k][0], w[k][1], tag)) {
                        const int br = k >> 1, q = (k & 1) * 2 + (lane >> 4), t = (lane & 1) * 2;
                        const uint32_t dst = sb + SM_A + ((br * 2 + ((lane >> 3) & 1)) * 4 + t) * 64 + ((q ^ ((t >> 1) + 2 * br)) << 4) +
                                             ((lane >> 1) & 3) * 4;
                        sts_u1(dst, (uint32_t)w[k][0]);
                        sts_u1(dst + 64, (uint32_t)w[k][1]);
                        pend &= ~(1u << k);
                    }
                if (__all_sync(~0u, pend == 0) || ++n >= SPIN_LIMIT) break;
                __nanosleep(200);
            }
            __syncwarp();
            if (lane == 0) mbar_arrive(bars + BAR_A * 8);
        }
        bar_sync(4, NCT + 32);
        {
            float mx = lds_f1(sb + SM_MAX + lane * 4);
            float sm = lds_f1(sb + SM_SUM + lane * 4);
#pragma unroll
            for (int o = 4; o < 32; o <<= 1) { mx = fmaxf(mx, __shfl_xor_sync(~0u, mx, o)); sm += __shfl_xor_sync(~0u, sm, o); }
            if (lane < 16)
                st_async_u32x2(sb + SM_INS + (sp * 4 + (lane & 3)) * 8, __float_as_uint(mx), __float_as_uint(sm), bars + BAR_ST * 8,
                               b * 4 + (lane >> 2));
        }
        float coef[4];
        {
            mbar_wait_cluster(bars + BAR_ST * 8);
            const float2 st = lds_f2(sb + SM_INS + (lane & 15) * 8);
            float gm = fmaxf(st.x, __shfl_xor_sync(~0u, st.x, 4));
            gm = fmaxf(gm, __shfl_xor_sync(~0u, gm, 8));
            const float wj = ex2((st.x - gm) * LOG2E);
            float gl = wj * st.y;
            gl += __shfl_xor_sync(~0u, gl, 4);
            gl += __shfl_xor_sync(~0u, gl, 8);
            const float cj = wj / gl;
#pragma unroll
            for (int k = 0; k < 4; k++) coef[k] = __shfl_sync(~0u, cj, k * 4 + ((lane >> 2) & 3));
        }
        mbar_wait_cluster(bars + BAR_PO * 8);
        {
            float4 o = make_float4(0.f, 0.f, 0.f, 0.f);
#pragma unroll
            for (int k = 0; k < 4; k++) {
                const float4 v = lds_f4(sb + SM_INB + k * 512 + lane * 16);
                o.x = fmaf(coef[k], v.x, o.x); o.y = fmaf(coef[k], v.y, o.y);
                o.z = fmaf(coef[k], v.z, o.z); o.w = fmaf(coef[k], v.w, o.w);
            }
            const int t = lane & 3, q = ((lane >> 2) & 3) * 2 + (sp >> 1);
            const uint32_t dst = sb + SM_O + ((b * 2 + (sp & 1)) * 4 + t) * 128 + ((q ^ (b * 4 + t)) << 4) + (lane >> 4) * 8;
            const uint32_t o0 = pack_bf16(o.x, o.y), o1 = pack_bf16(o.z, o.w);
#pragma unroll
            for (int k = 0; k < 8; k++) st_async_u32x2(dst, o0, o1, bars + BAR_O * 8, k);
        }
        if (rk >= 2) return;
        {
            float2 s = make_float2(bf_lo(xres), bf_hi(xres));
            const unsigned long long* src = &sc->pa[((rk * 8 + hkv) * 8) * 64 + lane * 2];
            unsigned long long v[8][2] = {};
            unsigned n = 0;
            bool fdone = false;
            auto take_ffn = [&]() {
                if (lane < 8)
                    asm volatile("mbarrier.arrive.relaxed.cluster.shared::cluster.b64 _, [%0];" ::"r"(mapa(bars + BAR_ACK * 8, lane)) : "memory");
                float2 f0 = make_float2(0.f, 0.f), f1 = f0;
#pragma unroll
                for (int i = 0; i < 16; i += 2) {
                    const float2 t0 = lds_f2(sb + SM_INF + i * 256 + lane * 8), t1 = lds_f2(sb + SM_INF + (i + 1) * 256 + lane * 8);
                    f0.x += t0.x; f0.y += t0.y; f1.x += t1.x; f1.y += t1.y;
                }
                s.x += f0.x + f1.x; s.y += f0.y + f1.y;
            };
            mbar_wait(bars + (CH_WO + 7) * 8);
            while (true) {
#pragma unroll
                for (int i = 0; i < 8; i++)
                    if (!tag_ok(v[i][0], v[i][1], tag)) ld_ll2(src + i * 64, v[i][0], v[i][1]);
                if (!fdone) {
                    uint32_t f;
                    asm volatile("{\n.reg .pred p;\nmbarrier.test_wait.parity.acquire.cluster.shared::cta.b64 p, [%1], 0;\nselp.u32 %0, 1, 0, p;\n}"
                                 : "=r"(f) : "r"(bars + BAR_F * 8) : "memory");
                    if (__all_sync(~0u, f)) { take_ffn(); fdone = true; }
                }
                bool ok = true;
#pragma unroll
                for (int i = 0; i < 8; i++) ok = ok && tag_ok(v[i][0], v[i][1], tag);
                if (__all_sync(~0u, ok) || ++n >= SPIN_LIMIT) break;
            }
            float2 a0 = make_float2(0.f, 0.f), a1 = a0;
#pragma unroll
            for (int i = 0; i < 8; i += 2) {
                a0.x += __uint_as_float((uint32_t)v[i][0]); a0.y += __uint_as_float((uint32_t)v[i][1]);
                a1.x += __uint_as_float((uint32_t)v[i + 1][0]); a1.y += __uint_as_float((uint32_t)v[i + 1][1]);
            }
            if (!fdone) {
                mbar_wait_cluster(bars + BAR_F * 8);
                take_ffn();
            }
            reinterpret_cast<uint32_t*>(p.out)[rk * 256 + hkv * 32 + lane] = pack_bf16(s.x + (a0.x + a1.x), s.y + (a0.y + a1.y));
            __syncwarp();
            if (c == 0 && lane == 0) sc->epoch = tag;
        }
        return;
    }

    const int u = warp;
    const int fg = lane >> 2, ft = lane & 3;

    uint32_t b1pair = 0;
    {
        uint4 v0 = make_uint4(0, 0, 0, 0), v1 = v0;
        if (u < 2) {
            const uint4* x4 = reinterpret_cast<const uint4*>(p.x) + u * 64 + lane * 2;
            v0 = __ldg(x4); v1 = __ldg(x4 + 1);
        }
        if (u == 2 && rk < 7) b1pair = __ldg(reinterpret_cast<const uint32_t*>(p.b1) + hkv * 112 + rk * 16 + (lane & 15));
        asm volatile("barrier.cluster.arrive.relaxed.aligned;" ::: "memory");
        if (u < 2) {
            const uint32_t a[8] = {v0.x, v0.y, v0.z, v0.w, v1.x, v1.y, v1.z, v1.w};
            float s0 = 0.f;
#pragma unroll
            for (int i = 0; i < 8; i++) s0 += bf_lo(a[i]) + bf_hi(a[i]);
#pragma unroll
            for (int o = 16; o > 0; o >>= 1) s0 += __shfl_xor_sync(~0u, s0, o);
            const float m0 = s0 * (1.f / D_MODEL);
            float q0 = 0.f;
#pragma unroll
            for (int i = 0; i < 8; i++) {
                float d;
                d = bf_lo(a[i]) - m0; q0 += d * d; d = bf_hi(a[i]) - m0; q0 += d * d;
            }
#pragma unroll
            for (int o = 16; o > 0; o >>= 1) q0 += __shfl_xor_sync(~0u, q0, o);
            const float mean = bf16r(m0);
            const float var = bf16r(q0 * (1.f / D_MODEL));
            const float den = bf16r(sqrtf(bf16r(var + 1e-5f)));
            const float rden = 1.f / den;
            uint32_t o[8];
#pragma unroll
            for (int i = 0; i < 8; i++) o[i] = pack_bf16(bf16r(bf_lo(a[i]) - mean) * rden, bf16r(bf_hi(a[i]) - mean) * rden);
            const uint32_t dst = sb + SM_XN + u * 1024 + lane * 32;
            sts_u4(dst, o[0], o[1], o[2], o[3]);
            sts_u4(dst + 16, o[4], o[5], o[6], o[7]);
        }
    }

    const int lrow = (lane & 7) + ((lane >> 4) << 3);
    const int lchk = (lane >> 3) & 1;
    const int hi = u >> 2;
    const uint32_t wa512 = sb + (hi * 32 + lrow) * 128 + ((((u & 3) * 2 + lchk) ^ (lrow & 7)) << 4);

    bar_sync(1, NTHREADS);
    const uint32_t tag = lds_u1(sb + SM_EPOCH);

    {
        uint32_t bb[8][4];
        const uint32_t xa = sb + SM_XN + (fg & 1) * 1024 + (hi * 16 + ft) * 4;
#pragma unroll
        for (int q = 0; q < 8; q++)
#pragma unroll
            for (int i = 0; i < 4; i++) bb[q][i] = lds_u1(xa + q * 128 + i * 16);
        float acc[4] = {}, acc2[4] = {};
        gemv_chunks<CH_WQ, true, 8>(acc, acc2, bb, wa512, bars, lane);
        if (ft == 0) {
            const uint32_t red = sb + SM_REDA + (hi * 128 + (u & 3) * 16 + fg) * 4;
            sts_f1(red, acc[0] + acc2[0]);
            sts_f1(red + 256, acc[1] + acc2[1]);
            sts_f1(red + 32, acc[2] + acc2[2]);
            sts_f1(red + 256 + 32, acc[3] + acc2[3]);
        }
    }
    asm volatile("barrier.cluster.wait.acquire.aligned;" ::: "memory");
    bar_sync(2, NCT);
    if (u < 2) {
        const float2 s0 = lds_f2(sb + SM_REDA + u * 256 + lane * 8), s1 = lds_f2(sb + SM_REDA + 512 + u * 256 + lane * 8);
        const uint32_t qp = pack_bf16(s0.x + s1.x, s0.y + s1.y);
        const uint32_t dst = sb + SM_Q + (((rk >> 1) * 4 + (lane & 3)) * 16 + (rk & 1) * 8 + (lane >> 2)) * 4;
#pragma unroll
        for (int k = 0; k < 4; k++) st_async_u32(dst, qp, bars + BAR_Q * 8, u * 4 + k);
    }

    if (rk < 7) {
        float acc[2][4] = {};
#pragma unroll
        for (int q = 0; q < 4; q++) {
            const uint32_t x0 = lds_u1(sb + SM_XN + (fg & 1) * 1024 + (q * 64 + u * 8 + ft) * 4);
            const uint32_t x1 = lds_u1(sb + SM_XN + (fg & 1) * 1024 + (q * 64 + u * 8 + 4 + ft) * 4);
            mbar_wait(bars + (CH_W1 + q) * 8);
            gemv_tile64(acc, sb + slot_off(CH_W1 + q), u * 16 + lrow, lchk, x0, x1);
            if (CH_W1 + q < NEMPTY && lane == 0) mbar_arrive(bars + (BAR_EMPTY + CH_W1 + q) * 8);
        }
        if (ft == 0) {
            const uint32_t rb = sb + SM_REDB + u * 256;
#pragma unroll
            for (int mt = 0; mt < 2; mt++) {
                sts_f1(rb + (mt * 16 + fg) * 4, acc[mt][0]);
                sts_f1(rb + 128 + (mt * 16 + fg) * 4, acc[mt][1]);
                sts_f1(rb + (mt * 16 + fg + 8) * 4, acc[mt][2]);
                sts_f1(rb + 128 + (mt * 16 + fg + 8) * 4, acc[mt][3]);
            }
        }
        if (u != 2) {
            bar_arrive(3, NCT);
        } else {
            bar_sync(3, NCT);
            float2 s = make_float2(0.f, 0.f);
#pragma unroll
            for (int k = 0; k < NCW; k++) {
                const float2 v = lds_f2(sb + SM_REDB + k * 256 + lane * 8);
                s.x += v.x; s.y += v.y;
            }
            const float h[2] = {bf16r(bf16r(s.x) + bf_lo(b1pair)), bf16r(bf16r(s.y) + bf_hi(b1pair))};
            float a[2];
#pragma unroll
            for (int i = 0; i < 2; i++) {
                const float e = bf16r(__expf(-fabsf(h[i])));
                const float sp_ = bf16r(bf16r(log1pf(e)) + fmaxf(h[i], 0.f));
                a[i] = h[i] * bf16r(tanhf(sp_));
            }
            st_ll1(&sc->ax[(hkv * 2 + (lane >> 4)) * 128 + rk * 16 + (lane & 15)], pack_bf16(a[0], a[1]), tag);
        }
    } else if (CH_W1 < NEMPTY && lane < 4) {
        mbar_arrive(bars + (BAR_EMPTY + CH_W1 + lane) * 8);
    }
    __syncwarp();

    {
        mbar_wait_cluster(bars + BAR_Q * 8);
        uint32_t qa[16];
#pragma unroll
        for (int i = 0; i < 4; i++) lds_u4(qa + 4 * i, sb + SM_Q + ((fg & 3) * 4 + ft) * 64 + i * 16);
        float sv[16];
        const float scale = 0.08838834764831845f;
#pragma unroll
        for (int h2 = 0; h2 < 2; h2++) {
            const int ch = CH_K + u + 8 * h2;
            mbar_wait(bars + ch * 8);
            float acc[4][4] = {};
            const uint32_t kb = sb + (ch % NSLOT) * 8192 + (lane & 7) * 128;
#pragma unroll
            for (int q = 0; q < 4; q++) {
                const int chunk = q * 4 + (lane >> 3);
                const uint32_t off = (chunk >> 3) * 4096 + (((chunk & 7) ^ (lane & 7)) << 4);
                uint32_t kf[4][4];
#pragma unroll
                for (int nt = 0; nt < 4; nt++) ldsm4(kf[nt], kb + nt * 1024 + off);
#pragma unroll
                for (int nt = 0; nt < 4; nt++) mma16816(acc[nt], qa[4 * q], 0u, qa[4 * q + 1], 0u, kf[nt][0], kf[nt][1]);
#pragma unroll
                for (int nt = 0; nt < 4; nt++) mma16816(acc[nt], qa[4 * q + 2], 0u, qa[4 * q + 3], 0u, kf[nt][2], kf[nt][3]);
            }
            if (lane == 0) mbar_arrive(bars + (BAR_EMPTY + ch) * 8);
#pragma unroll
            for (int i = 0; i < 8; i++) sv[h2 * 8 + i] = bf16r(bf16r(acc[i >> 1][i & 1]) * scale);
        }
        float m = sv[0];
#pragma unroll
        for (int i = 1; i < 16; i++) m = fmaxf(m, sv[i]);
        m = fmaxf(m, __shfl_xor_sync(~0u, m, 1));
        m = fmaxf(m, __shfl_xor_sync(~0u, m, 2));
        if (lane < 16 && ft == 0) sts_f1(sb + SM_MAX + (u * 4 + fg) * 4, m);
        bar_sync(2, NCT);
        m = lds_f1(sb + SM_MAX + ((ft + 4 * (fg >> 2)) * 4 + (fg & 3)) * 4);
        m = fmaxf(m, __shfl_xor_sync(~0u, m, 1));
        m = fmaxf(m, __shfl_xor_sync(~0u, m, 2));
        m = fmaxf(m, __shfl_xor_sync(~0u, m, 16));
        float l = 0.f;
#pragma unroll
        for (int i = 0; i < 16; i++) { sv[i] = ex2((sv[i] - m) * LOG2E); l += sv[i]; }
        l += __shfl_xor_sync(~0u, l, 1);
        l += __shfl_xor_sync(~0u, l, 2);
        if (lane < 16) {
#pragma unroll
            for (int h2 = 0; h2 < 2; h2++)
                sts_u4(sb + SM_P + ((u + 8 * h2) * 16 + lane) * 16, pack_bf16(sv[h2 * 8], sv[h2 * 8 + 1]),
                       pack_bf16(sv[h2 * 8 + 2], sv[h2 * 8 + 3]), pack_bf16(sv[h2 * 8 + 4], sv[h2 * 8 + 5]),
                       pack_bf16(sv[h2 * 8 + 6], sv[h2 * 8 + 7]));
            if (ft == 0) sts_f1(sb + SM_SUM + (u * 4 + fg) * 4, l);
        }
        bar_arrive(4, NCT + 32);
        bar_sync(2, NCT);
    }

    {
        float acc[2][4] = {}, acc2[2][4] = {};
        const uint32_t voff = sb + (u >> 2) * 4096 + lane * 128;
        const uint32_t c0 = (((u & 3) * 2) ^ (lane & 7)) << 4, c1 = (((u & 3) * 2 + 1) ^ (lane & 7)) << 4;
#pragma unroll
        for (int i = 0; i < 16; i++) {
            uint32_t pa[4], v0[4], v1[4];
            lds_u4(pa, sb + SM_P + (i * 16 + (lane & 15)) * 16);
            mbar_wait(bars + (CH_V + i) * 8);
            ldsm4t(v0, voff + slot_off(CH_V + i) + c0);
            ldsm4t(v1, voff + slot_off(CH_V + i) + c1);
            mma16816(acc[0], pa[0], 0u, pa[1], 0u, v0[0], v0[1]);
            mma16816(acc[1], pa[0], 0u, pa[1], 0u, v1[0], v1[1]);
            mma16816(acc2[0], pa[2], 0u, pa[3], 0u, v0[2], v0[3]);
            mma16816(acc2[1], pa[2], 0u, pa[3], 0u, v1[2], v1[3]);
            if (CH_V + i < NEMPTY && lane == 0) mbar_arrive(bars + (BAR_EMPTY + CH_V + i) * 8);
        }
        if (lane < 16) {
            const uint32_t rank = b * 4 + (u >> 1);
            asm volatile("st.async.weak.shared::cluster.mbarrier::complete_tx::bytes.v4.f32 [%0], {%1, %2, %3, %4}, [%5];"
                         ::"r"(mapa(sb + SM_INB + sp * 512 + (u & 1) * 256 + lane * 16, rank)), "f"(acc[0][0] + acc2[0][0]),
                           "f"(acc[0][1] + acc2[0][1]), "f"(acc[1][0] + acc2[1][0]), "f"(acc[1][1] + acc2[1][1]),
                           "r"(mapa(bars + BAR_PO * 8, rank)) : "memory");
        }
    }

    {
        float acc[4] = {}, acc2[4] = {};
        uint32_t a0[NPRE][4], a1[NPRE][4];
#pragma unroll
        for (int q = 0; q < NPRE; q++) {
            mbar_wait(bars + (CH_WO + q) * 8);
            ldsm4t(a0[q], wa512 + slot_off(CH_WO + q));
            ldsm4t(a1[q], wa512 + slot_off(CH_WO + q) + 2048);
        }
        mbar_wait_cluster(bars + BAR_O * 8);
        uint32_t bb[8][4];
#pragma unroll
        for (int q = 0; q < 8; q++)
            lds_u4(bb[q], sb + SM_O + (((fg & 1) * 2 + hi) * 4 + ft) * 128 + ((q ^ ((fg & 1) * 4 + ft)) << 4));
        float acc3[4] = {}, acc4[4] = {};
#pragma unroll
        for (int q = 0; q < NPRE; q++) {
            float(&x)[4] = (q & 1) ? acc3 : acc;
            float(&y)[4] = (q & 1) ? acc4 : acc2;
            mma16816(x, a0[q][0], a0[q][1], a0[q][2], a0[q][3], bb[q][0], bb[q][1]);
            mma16816(y, a1[q][0], a1[q][1], a1[q][2], a1[q][3], bb[q][2], bb[q][3]);
        }
        float tl[8 - NPRE][2][4] = {};
        {
            uint32_t t0[8 - NPRE][4], t1[8 - NPRE][4];
#pragma unroll
            for (int q = NPRE; q < 8; q++) {
                mbar_wait(bars + (CH_WO + q) * 8);
                ldsm4t(t0[q - NPRE], wa512 + slot_off(CH_WO + q));
                ldsm4t(t1[q - NPRE], wa512 + slot_off(CH_WO + q) + 2048);
            }
#pragma unroll
            for (int i = 0; i < 4; i++) acc[i] = (acc[i] + acc3[i]) + (acc2[i] + acc4[i]);
#pragma unroll
            for (int q = NPRE; q < 8; q++) {
                const int k = q - NPRE;
                mma16816(tl[k][0], t0[k][0], t0[k][1], t0[k][2], t0[k][3], bb[q][0], bb[q][1]);
                mma16816(tl[k][1], t1[k][0], t1[k][1], t1[k][2], t1[k][3], bb[q][2], bb[q][3]);
            }
        }
#pragma unroll
        for (int i = 0; i < 4; i++) {
            acc2[i] = 0.f;
#pragma unroll
            for (int k = 0; k < 8 - NPRE; k++) acc2[i] += tl[k][0][i] + tl[k][1][i];
        }
        if (ft == 0) {
            const uint32_t red = sb + SM_REDA + (hi * 128 + (u & 3) * 16 + fg) * 4;
            sts_f1(red, acc[0] + acc2[0]);
            sts_f1(red + 256, acc[1] + acc2[1]);
            sts_f1(red + 32, acc[2] + acc2[2]);
            sts_f1(red + 256 + 32, acc[3] + acc2[3]);
        }
    }
    if (u >= 2) {
        bar_arrive(2, NCT);
    } else {
        bar_sync(2, NCT);
        const float2 s0 = lds_f2(sb + SM_REDA + u * 256 + lane * 8), s1 = lds_f2(sb + SM_REDA + 512 + u * 256 + lane * 8);
        st_ll2(&sc->pa[((u * 8 + rk) * 8 + hkv) * 64 + lane * 2], __float_as_uint(s0.x + s1.x), __float_as_uint(s0.y + s1.y), tag);
    }

    {
        float acc[4] = {}, acc2[4] = {};
        uint32_t ba[4][4];
        mbar_wait(bars + BAR_A * 8);
#pragma unroll
        for (int q = 0; q < 4; q++)
            lds_u4(ba[q], sb + SM_A + (((fg & 1) * 2 + hi) * 4 + ft) * 64 + ((q ^ ((ft >> 1) + 2 * (fg & 1))) << 4));
        float acc3[4] = {}, acc4[4] = {};
        {
            uint32_t t0[4][4], t1[4][4];
#pragma unroll
            for (int q = 0; q < 3; q++) {
                mbar_wait(bars + (CH_W2 + q) * 8);
                ldsm4t(t0[q], wa512 + slot_off(CH_W2 + q));
                ldsm4t(t1[q], wa512 + slot_off(CH_W2 + q) + 2048);
            }
            mma16816(acc, t0[0][0], t0[0][1], t0[0][2], t0[0][3], ba[0][0], ba[0][1]);
            mma16816(acc2, t1[0][0], t1[0][1], t1[0][2], t1[0][3], ba[0][2], ba[0][3]);
            mma16816(acc3, t0[1][0], t0[1][1], t0[1][2], t0[1][3], ba[1][0], ba[1][1]);
            mma16816(acc4, t1[1][0], t1[1][1], t1[1][2], t1[1][3], ba[1][2], ba[1][3]);
            if (hi == 0) {
                mbar_wait(bars + (CH_W2 + 3) * 8);
                ldsm4t(t0[3], wa512 + slot_off(CH_W2 + 3));
                ldsm4t(t1[3], wa512 + slot_off(CH_W2 + 3) + 2048);
            }
            mma16816(acc, t0[2][0], t0[2][1], t0[2][2], t0[2][3], ba[2][0], ba[2][1]);
            mma16816(acc2, t1[2][0], t1[2][1], t1[2][2], t1[2][3], ba[2][2], ba[2][3]);
            if (hi == 0) {
                mma16816(acc3, t0[3][0], t0[3][1], t0[3][2], t0[3][3], ba[3][0], ba[3][1]);
                mma16816(acc4, t1[3][0], t1[3][1], t1[3][2], t1[3][3], ba[3][2], ba[3][3]);
            }
        }
#pragma unroll
        for (int i = 0; i < 4; i++) { acc[i] += acc3[i]; acc2[i] += acc4[i]; }
        if (ft == 0) {
            const uint32_t dst = sb + SM_INF + ((rk * 2 + hi) * 64 + (u & 3) * 16 + fg) * 4;
            st_async_u32(dst, __float_as_uint(acc[0] + acc2[0]), bars + BAR_F * 8, 0);
            st_async_u32(dst, __float_as_uint(acc[1] + acc2[1]), bars + BAR_F * 8, 1);
            st_async_u32(dst + 32, __float_as_uint(acc[2] + acc2[2]), bars + BAR_F * 8, 0);
            st_async_u32(dst + 32, __float_as_uint(acc[3] + acc2[3]), bars + BAR_F * 8, 1);
        }
    }
    if (u == 0) mbar_wait(bars + BAR_ACK * 8);
}

typedef CUresult (*EncodeTiledFn)(CUtensorMap*, CUtensorMapDataType, cuuint32_t, void*, const cuuint64_t*, const cuuint64_t*,
                                  const cuuint32_t*, const cuuint32_t*, CUtensorMapInterleave, CUtensorMapSwizzle,
                                  CUtensorMapL2promotion, CUtensorMapFloatOOBfill);

void make_map(EncodeTiledFn enc, CUtensorMap* m, const void* base, uint64_t cols, uint64_t rows, uint32_t box_c, uint32_t box_r,
              CUtensorMapSwizzle sw) {
    cuuint64_t gd[2] = {cols, rows};
    cuuint64_t gs[1] = {cols * 2};
    cuuint32_t bd[2] = {box_c, box_r};
    cuuint32_t es[2] = {1, 1};
    enc(m, CU_TENSOR_MAP_DATA_TYPE_BFLOAT16, 2, const_cast<void*>(base), gd, gs, bd, es, CU_TENSOR_MAP_INTERLEAVE_NONE, sw,
        CU_TENSOR_MAP_L2_PROMOTION_L2_128B, CU_TENSOR_MAP_FLOAT_OOB_FILL_NONE);
}

}

extern "C" void kernel_launch(void* const* d_in, const int* in_sizes, int n_in, void* d_out, int out_size) {
    (void)in_sizes; (void)n_in; (void)out_size;
    static EncodeTiledFn enc = nullptr;
    static Scratch* sc = nullptr;
    if (!enc) {
        void* fn = nullptr;
        cudaDriverEntryPointQueryResult st;
        cudaGetDriverEntryPoint("cuTensorMapEncodeTiled", &fn, cudaEnableDefault, &st);
        enc = (EncodeTiledFn)fn;
        cudaFuncSetAttribute(fused_decode_kernel, cudaFuncAttributeMaxDynamicSharedMemorySize, SM_TOTAL);
        void* sp = nullptr;
        cudaGetSymbolAddress(&sp, g_scratch);
        sc = (Scratch*)sp;
    }
    Params p;
    make_map(enc, &p.k, d_in[1], 128, 2 * 8 * SK, 64, 32, CU_TENSOR_MAP_SWIZZLE_128B);
    make_map(enc, &p.v, d_in[2], 128, 2 * 8 * SK, 64, 32, CU_TENSOR_MAP_SWIZZLE_128B);
    make_map(enc, &p.wq, d_in[3], 4096, 512, 64, 64, CU_TENSOR_MAP_SWIZZLE_128B);
    make_map(enc, &p.wo, d_in[4], 512, 4096, 64, 64, CU_TENSOR_MAP_SWIZZLE_128B);
    make_map(enc, &p.w1, d_in[6], FF, 512, 32, 128, CU_TENSOR_MAP_SWIZZLE_64B);
    make_map(enc, &p.w2, d_in[8], 512, FF, 64, 32, CU_TENSOR_MAP_SWIZZLE_128B);
    p.x = (const __nv_bfloat16*)d_in[0];
    p.b1 = (const __nv_bfloat16*)d_in[7];
    p.out = (__nv_bfloat16*)d_out;
    p.sc = sc;
    fused_decode_kernel<<<NCTA, NTHREADS, SM_TOTAL, cudaStreamPerThread>>>(p);
}
```
